```python
import torch

def _softmax(x, axis=-1):
    return torch.softmax(x, dim=axis)
def _gelu(x):
    return torch.nn.functional.gelu(x, approximate="tanh")
def _silu(x):
    return torch.nn.functional.silu(x)
def _sigmoid(x):
    return torch.sigmoid(x)
def _layernorm(x, axis=-1, eps=1e-5):
    m = x.mean(dim=axis, keepdim=True)
    v = x.var(dim=axis, keepdim=True, unbiased=False)
    return (x - m) / torch.sqrt(v + eps)
def _scatter_add(tgt, idx, src, axis=0):
    return tgt.clone().index_add_(axis, idx, src)
def _segment_sum(src, seg, n):
    out = torch.zeros((n,) + src.shape[1:], dtype=src.dtype)
    return out.index_add_(0, seg, src)
def _pad(x, pw):
    flat = tuple(v for pair in reversed(pw) for v in pair)
    return torch.nn.functional.pad(x, flat)

kernel_name = 'gated_mix__compressed_kv_cla__geglu_ffn__prompt'

def setup_inputs():

    _w = (lambda a: (lambda t: t.to(torch.bfloat16) if t.is_floating_point() else t)(torch.as_tensor(a)))
    def _A_setup():
        B, H, Sq, Sk, D, M = 1, 32, 2048, 2048, 128, 512
        Dc = 4 * D
        return {
            "x": _w((lambda *s: torch.randn(*s, dtype=torch.bfloat16) * 0.05)(B, Sq, M)),
            "c_kv": _w((lambda *s: torch.randn(*s, dtype=torch.bfloat16) * 0.8)(B, Sk, Dc)),
            "w_q": _w((lambda *s: torch.randn(*s, dtype=torch.bfloat16) * 6.4)(M, H, D) * (M ** -0.5)),
            "w_uk": _w((lambda *s: torch.randn(*s, dtype=torch.bfloat16) * 6.4)(Dc, H, D) * (Dc ** -0.5)),
            "w_uv": _w((lambda *s: torch.randn(*s, dtype=torch.bfloat16) * 0.8)(Dc, H, D) * (Dc ** -0.5)),
            "w_o": _w((lambda *s: torch.randn(*s, dtype=torch.bfloat16) * 0.8)(H, D, M) * ((H * D) ** -0.5)),
        }
    _A_in = _A_setup()

    def _B_setup():
        B, S, D, F = 1, 2048, 512, 1792
        return {
            "x": _w((lambda *s: torch.randn(*s, dtype=torch.bfloat16) * 0.05)(B, S, D)),
            "w_gate": _w((lambda *s: torch.randn(*s, dtype=torch.bfloat16) * 0.2)(D, F)),
            "w_up": _w((lambda *s: torch.randn(*s, dtype=torch.bfloat16) * 0.2)(D, F)),
            "w_down": _w((lambda *s: torch.randn(*s, dtype=torch.bfloat16) * 0.2)(F, D)),
        }
    _B_in = _B_setup()

    return {
        "A_x": _A_in["x"],
        "A_c_kv": _A_in["c_kv"],
        "A_w_q": _A_in["w_q"],
        "A_w_uk": _A_in["w_uk"],
        "A_w_uv": _A_in["w_uv"],
        "A_w_o": _A_in["w_o"],
        "B_x": _B_in["x"],
        "B_w_gate": _B_in["w_gate"],
        "B_w_up": _B_in["w_up"],
        "B_w_down": _B_in["w_down"],
        "gate_w": _w((lambda *s: torch.randn(*s, dtype=torch.bfloat16) * 0.05)(512) * 16.0),
    }

def reference(A_x, A_c_kv, A_w_q, A_w_uk, A_w_uv, A_w_o, B_x, B_w_gate, B_w_up, B_w_down, gate_w):
    def _A_ref(x, c_kv, w_q, w_uk, w_uv, w_o):
        B, Sq, M = x.shape[0], x.shape[1], x.shape[2]
        Sk = c_kv.shape[1]
        H, D = w_q.shape[1], w_q.shape[2]
        q = torch.einsum("bqm,mhd->bhqd", x, w_q)
        k = torch.einsum("bkc,chd->bhkd", c_kv, w_uk)
        v = torch.einsum("bkc,chd->bhkd", c_kv, w_uv)
        scores = torch.einsum("bhqd,bhkd->bhqk", q, k) * (D ** -0.5)
        off = Sk - Sq
        qi = torch.arange(Sq)[:, None]
        kj = torch.arange(Sk)[None, :]
        cmask = kj <= (qi + off)
        scores = torch.where(cmask[None, None], scores, -1e9)
        p = _softmax(scores, axis=-1)
        ctx = torch.einsum("bhqk,bhkd->bhqd", p, v)
        return torch.einsum("bhqd,hdm->bqm", ctx, w_o)

    def _B_ref(x, w_gate, w_up, w_down):
        return (_gelu(x @ w_gate) * (x @ w_up)) @ w_down

    x = A_x
    g = _sigmoid((x * gate_w).sum(-1, keepdims=True))
    a = _A_ref(x, A_c_kv, A_w_q, A_w_uk, A_w_uv, A_w_o)
    b = _B_ref(x, B_w_gate, B_w_up, B_w_down)
    return g * a + (1 - g) * b
```

```cpp
#include <cuda_runtime.h>
#include <cuda_bf16.h>
#include <cuda.h>
#include <stdint.h>

namespace {

constexpr int SEQ = 2048, DM = 512, NH = 32, FF = 1792;
constexpr int MAXCL = 66;
constexpr int MAXIT = 20;

constexpr int NSLOT = 6, SLOT_BYTES = 32768;
constexpr int RING_BYTES = NSLOT * SLOT_BYTES;
constexpr int STG_OFF = RING_BYTES;
constexpr int BAR_OFF = STG_OFF + 32768;
constexpr int B_FULL = BAR_OFF, B_EMPTY = B_FULL + 8 * NSLOT;
constexpr int B_STGF = B_EMPTY + 8 * NSLOT, B_STGE = B_STGF + 16;
constexpr int B_GATE = B_STGE + 16;
constexpr int B_DEP = B_GATE + 16;
constexpr int B_ISS = B_DEP + 4;
constexpr int SMEM_BYTES = BAR_OFF + 256 + 1024;
#define PF_DIST 24
#define PF_MODE 0
#define GATE_DELAY 2
#define SCHED 2

constexpr int FL_KV = 0;
constexpr int FL_A = FL_KV + 256;
constexpr int FL_G = FL_A + 46 * 8;
constexpr int FL_Z = FL_G + 1;
constexpr int FL_TICKET = FL_Z + 1;
constexpr int FL_TOTAL = FL_TICKET + 1;

enum { TM_X64 = 0, TM_X, TM_C, TM_WQ, TM_WUK, TM_WUV, TM_WO, TM_WG, TM_WU, TM_WD, TM_OUT, TM_COUNT };
enum { IT_KV = 0, IT_UP = 1, IT_ATT = 2, IT_FIN = 3 };
constexpr uint16_t IT_END = 0xFFFF;

struct Params {
  CUtensorMap tm[TM_COUNT];
  const __nv_bfloat16* x;
  const __nv_bfloat16* c;
  const __nv_bfloat16* gate_w;
  __nv_bfloat16* out;
  const void* w[7];
  uint32_t fin[MAXCL];
  uint16_t sched[MAXCL * MAXIT];
};

__device__ __align__(1024) uint8_t g_kv[2 * NH * 16 * 32768];
__device__ __align__(1024) uint8_t g_a[16 * 92 * 16384];
__device__ float g_gate[SEQ];
__device__ unsigned g_flags[FL_TOTAL];
__device__ unsigned g_abort;
#define PROF(slot, idx)
#define PROFG(slot, idx)
#define PROFX(slot, idx)

__device__ __forceinline__ uint32_t smem_u32(const void* p) { return (uint32_t)__cvta_generic_to_shared(p); }
__device__ __forceinline__ void mbar_init(uint32_t bar, uint32_t cnt) {
  asm volatile("mbarrier.init.shared::cta.b64 [%0], %1;" ::"r"(bar), "r"(cnt));
}
__device__ __forceinline__ void mbar_expect_tx(uint32_t bar, uint32_t bytes) {
  asm volatile("mbarrier.arrive.expect_tx.shared::cta.b64 _, [%0], %1;" ::"r"(bar), "r"(bytes) : "memory");
}
__device__ __forceinline__ uint32_t mapa(uint32_t addr, uint32_t cta) {
  uint32_t r;
  asm("mapa.shared::cluster.u32 %0, %1, %2;" : "=r"(r) : "r"(addr), "r"(cta));
  return r;
}
__device__ __forceinline__ void mbar_arrive_cluster(uint32_t cbar) {
  asm volatile("mbarrier.arrive.shared::cluster.b64 _, [%0];" ::"r"(cbar) : "memory");
}
__device__ __forceinline__ bool mbar_try(uint32_t bar, uint32_t parity) {
  uint32_t ok;
  asm volatile("{\n.reg .pred p;\nmbarrier.try_wait.parity.shared::cta.b64 p, [%1], %2;\nselp.u32 %0, 1, 0, p;\n}"
               : "=r"(ok) : "r"(bar), "r"(parity) : "memory");
  return ok != 0;
}
__device__ __forceinline__ bool wait_giveup(uint32_t& n) {
  if ((++n & 1023u) != 0) return false;
  if (n > (1u << 21)) *((volatile unsigned*)&g_abort) = 1;
  return *((volatile unsigned*)&g_abort) != 0;
}
__device__ __forceinline__ void mbar_wait(uint32_t bar, uint32_t parity) {
  if (mbar_try(bar, parity)) return;
  uint32_t n = 0;
  while (!mbar_try(bar, parity)) {
    if (wait_giveup(n)) break;
  }
}
__device__ __forceinline__ void tma_load_2d(uint32_t dst, const CUtensorMap* tm, int c0, int c1, uint32_t bar) {
  asm volatile("cp.async.bulk.tensor.2d.shared::cluster.global.mbarrier::complete_tx::bytes [%0], [%1, {%3, %4}], [%2];"
               ::"r"(dst), "l"(tm), "r"(bar), "r"(c0), "r"(c1) : "memory");
}
__device__ __forceinline__ void tma_load_2d_mc(uint32_t dst, const CUtensorMap* tm, int c0, int c1, uint32_t bar) {
  asm volatile("cp.async.bulk.tensor.2d.shared::cluster.global.mbarrier::complete_tx::bytes.multicast::cluster [%0], [%1, {%3, %4}], [%2], %5;"
               ::"r"(dst), "l"(tm), "r"(bar), "r"(c0), "r"(c1), "h"((uint16_t)3) : "memory");
}
__device__ __forceinline__ void bulk_load(uint32_t dst, const void* src, uint32_t bytes, uint32_t bar) {
  asm volatile("cp.async.bulk.shared::cluster.global.mbarrier::complete_tx::bytes [%0], [%1], %2, [%3];"
               ::"r"(dst), "l"(src), "r"(bytes), "r"(bar) : "memory");
}
__device__ __forceinline__ void bulk_load_mc(uint32_t dst, const void* src, uint32_t bytes, uint32_t bar) {
  asm volatile("cp.async.bulk.shared::cluster.global.mbarrier::complete_tx::bytes.multicast::cluster [%0], [%1], %2, [%3], %4;"
               ::"r"(dst), "l"(src), "r"(bytes), "r"(bar), "h"((uint16_t)3) : "memory");
}
__device__ __forceinline__ void bulk_store(void* dst, uint32_t src, uint32_t bytes) {
  asm volatile("cp.async.bulk.global.shared::cta.bulk_group [%0], [%1], %2;" ::"l"(dst), "r"(src), "r"(bytes) : "memory");
}
__device__ __forceinline__ void tma_reduce_add_2d(const CUtensorMap* tm, int c0, int c1, uint32_t src) {
  asm volatile("cp.reduce.async.bulk.tensor.2d.global.shared::cta.add.tile.bulk_group [%0, {%2, %3}], [%1];"
               ::"l"(tm), "r"(src), "r"(c0), "r"(c1) : "memory");
}
__device__ __forceinline__ void tma_prefetch_2d(const CUtensorMap* tm, int c0, int c1) {
  asm volatile("cp.async.bulk.prefetch.tensor.2d.L2.global.tile [%0, {%1, %2}];" ::"l"(tm), "r"(c0), "r"(c1) : "memory");
}
__device__ __forceinline__ void bulk_prefetch(const void* src, uint32_t bytes) {
  asm volatile("cp.async.bulk.prefetch.L2.global [%0], %1;" ::"l"(src), "r"(bytes) : "memory");
}
__device__ __forceinline__ void bulk_commit() { asm volatile("cp.async.bulk.commit_group;" ::: "memory"); }
__device__ __forceinline__ void bulk_wait_read() { asm volatile("cp.async.bulk.wait_group.read 0;" ::: "memory"); }
__device__ __forceinline__ void bulk_wait_all() { asm volatile("cp.async.bulk.wait_group 0;" ::: "memory"); }
__device__ __forceinline__ void fence_async_smem() { asm volatile("fence.proxy.async.shared::cta;" ::: "memory"); }
__device__ __forceinline__ void fence_async_global() { asm volatile("fence.proxy.async.global;" ::: "memory"); }
__device__ __forceinline__ void mbar_arrive(uint32_t bar) {
  asm volatile("mbarrier.arrive.shared::cta.b64 _, [%0];" ::"r"(bar) : "memory");
}
__device__ __forceinline__ void st_release_smem(uint32_t addr, uint32_t v) {
  asm volatile("st.release.cta.shared.u32 [%0], %1;" ::"r"(addr), "r"(v) : "memory");
}
__device__ __forceinline__ uint32_t ld_acquire_smem(uint32_t addr) {
  uint32_t v;
  asm volatile("ld.acquire.cta.shared.u32 %0, [%1];" : "=r"(v) : "r"(addr) : "memory");
  return v;
}
__device__ __forceinline__ void red_release(unsigned* p, unsigned v) {
  asm volatile("red.release.gpu.global.add.u32 [%0], %1;" ::"l"(p), "r"(v) : "memory");
}
__device__ __forceinline__ unsigned ld_acquire(const unsigned* p) {
  unsigned v;
  asm volatile("ld.acquire.gpu.global.u32 %0, [%1];" : "=r"(v) : "l"(p) : "memory");
  return v;
}
__device__ __forceinline__ void flag_wait(const unsigned* p, unsigned target) {
  uint32_t n = 0;
  while (ld_acquire(p) < target) {
    __nanosleep(64);
    if (wait_giveup(n)) break;
  }
}
__device__ __forceinline__ void dep_wait(uint32_t addr, uint32_t target) {
  uint32_t n = 0;
  while (ld_acquire_smem(addr) < target) {
    __nanosleep(32);
    if (wait_giveup(n)) break;
  }
}
__device__ __forceinline__ void cluster_sync() {
  asm volatile("barrier.cluster.arrive.release.aligned;\nbarrier.cluster.wait.acquire.aligned;" ::: "memory");
}
__device__ __forceinline__ void cluster_sync_relaxed() {
  asm volatile("barrier.cluster.arrive.relaxed.aligned;\nbarrier.cluster.wait.aligned;" ::: "memory");
}
__device__ __forceinline__ float ex2(float x) {
  float y;
  asm("ex2.approx.ftz.f32 %0, %1;" : "=f"(y) : "f"(x));
  return y;
}
__device__ __forceinline__ float tanh_fast(float x) {
  float y;
  asm("tanh.approx.f32 %0, %1;" : "=f"(y) : "f"(x));
  return y;
}
__device__ __forceinline__ uint32_t pack_bf16(float lo, float hi) {
  uint32_t r;
  asm("cvt.rn.bf16x2.f32 %0, %1, %2;" : "=r"(r) : "f"(hi), "f"(lo));
  return r;
}
__device__ __forceinline__ void stsm4(uint32_t addr, uint32_t a, uint32_t b, uint32_t c, uint32_t d) {
  asm volatile("stmatrix.sync.aligned.m8n8.x4.shared.b16 [%0], {%1, %2, %3, %4};" ::"r"(addr), "r"(a), "r"(b), "r"(c), "r"(d) : "memory");
}

__device__ __forceinline__ uint64_t mk_desc(uint32_t a16, uint32_t off, uint32_t lbo) {
  uint32_t lo = a16 + ((off >> 4) | ((lbo >> 4) << 16));
  uint32_t hi = (1024 >> 4) | (1u << 30);
  return ((uint64_t)hi << 32) | lo;
}

#define WG_FENCE() asm volatile("wgmma.fence.sync.aligned;" ::: "memory")
#define WG_COMMIT() asm volatile("wgmma.commit_group.sync.aligned;" ::: "memory")
#define WG_WAIT(n) asm volatile("wgmma.wait_group.sync.aligned %0;" ::"n"(n) : "memory")
#define R8(d, b) "+f"(d[b + 0]), "+f"(d[b + 1]), "+f"(d[b + 2]), "+f"(d[b + 3]), "+f"(d[b + 4]), "+f"(d[b + 5]), "+f"(d[b + 6]), "+f"(d[b + 7])
#define W8(d, b) "=f"(d[b + 0]), "=f"(d[b + 1]), "=f"(d[b + 2]), "=f"(d[b + 3]), "=f"(d[b + 4]), "=f"(d[b + 5]), "=f"(d[b + 6]), "=f"(d[b + 7])
#define REGS128 "{%0,%1,%2,%3,%4,%5,%6,%7,%8,%9,%10,%11,%12,%13,%14,%15,%16,%17,%18,%19,%20,%21,%22,%23,%24,%25,%26,%27,%28,%29,%30,%31," \
               "%32,%33,%34,%35,%36,%37,%38,%39,%40,%41,%42,%43,%44,%45,%46,%47,%48,%49,%50,%51,%52,%53,%54,%55,%56,%57,%58,%59,%60,%61,%62,%63," \
               "%64,%65,%66,%67,%68,%69,%70,%71,%72,%73,%74,%75,%76,%77,%78,%79,%80,%81,%82,%83,%84,%85,%86,%87,%88,%89,%90,%91,%92,%93,%94,%95," \
               "%96,%97,%98,%99,%100,%101,%102,%103,%104,%105,%106,%107,%108,%109,%110,%111,%112,%113,%114,%115,%116,%117,%118,%119,%120,%121,%122,%123,%124,%125,%126,%127}"
#define REGS64 "{%0,%1,%2,%3,%4,%5,%6,%7,%8,%9,%10,%11,%12,%13,%14,%15,%16,%17,%18,%19,%20,%21,%22,%23,%24,%25,%26,%27,%28,%29,%30,%31," \
               "%32,%33,%34,%35,%36,%37,%38,%39,%40,%41,%42,%43,%44,%45,%46,%47,%48,%49,%50,%51,%52,%53,%54,%55,%56,%57,%58,%59,%60,%61,%62,%63}"

template <int V> struct IC { static constexpr int value = V; };
template <int N>
__device__ __forceinline__ void reg_fence(float (&d)[N]) {
#pragma unroll
  for (int i = 0; i < N; i++) asm volatile("" : "+f"(d[i])::"memory");
}
template <int N>
__device__ __forceinline__ void reg_fence_u(uint32_t (&d)[N]) {
#pragma unroll
  for (int i = 0; i < N; i++) asm volatile("" : "+r"(d[i])::"memory");
}

template <int TB, int INIT>
__device__ __forceinline__ void wgmma_ss_n128(float (&d)[64], uint64_t da, uint64_t db) {
  if (INIT)
    asm volatile("wgmma.mma_async.sync.aligned.m64n128k16.f32.bf16.bf16 " REGS64 ", %64, %65, 0, 1, 1, 0, %66;\n"
                 : W8(d, 0), W8(d, 8), W8(d, 16), W8(d, 24), W8(d, 32), W8(d, 40), W8(d, 48), W8(d, 56)
                 : "l"(da), "l"(db), "n"(TB));
  else
    asm volatile("wgmma.mma_async.sync.aligned.m64n128k16.f32.bf16.bf16 " REGS64 ", %64, %65, 1, 1, 1, 0, %66;\n"
                 : R8(d, 0), R8(d, 8), R8(d, 16), R8(d, 24), R8(d, 32), R8(d, 40), R8(d, 48), R8(d, 56)
                 : "l"(da), "l"(db), "n"(TB));
}
template <int TB, int INIT>
__device__ __forceinline__ void wgmma_rs_n128(float (&d)[64], uint32_t a0, uint32_t a1, uint32_t a2, uint32_t a3, uint64_t db) {
  if (INIT)
    asm volatile("wgmma.mma_async.sync.aligned.m64n128k16.f32.bf16.bf16 " REGS64 ", {%64,%65,%66,%67}, %68, 0, 1, 1, %69;\n"
                 : W8(d, 0), W8(d, 8), W8(d, 16), W8(d, 24), W8(d, 32), W8(d, 40), W8(d, 48), W8(d, 56)
                 : "r"(a0), "r"(a1), "r"(a2), "r"(a3), "l"(db), "n"(TB));
  else
    asm volatile("wgmma.mma_async.sync.aligned.m64n128k16.f32.bf16.bf16 " REGS64 ", {%64,%65,%66,%67}, %68, 1, 1, 1, %69;\n"
                 : R8(d, 0), R8(d, 8), R8(d, 16), R8(d, 24), R8(d, 32), R8(d, 40), R8(d, 48), R8(d, 56)
                 : "r"(a0), "r"(a1), "r"(a2), "r"(a3), "l"(db), "n"(TB));
}
template <int INIT>
__device__ __forceinline__ void wgmma_ss_n256(float (&d)[128], uint64_t da, uint64_t db) {
  if (INIT)
    asm volatile("wgmma.mma_async.sync.aligned.m64n256k16.f32.bf16.bf16 " REGS128 ", %128, %129, 0, 1, 1, 0, 1;\n"
                 : W8(d, 0), W8(d, 8), W8(d, 16), W8(d, 24), W8(d, 32), W8(d, 40), W8(d, 48), W8(d, 56),
                   W8(d, 64), W8(d, 72), W8(d, 80), W8(d, 88), W8(d, 96), W8(d, 104), W8(d, 112), W8(d, 120)
                 : "l"(da), "l"(db));
  else
    asm volatile("wgmma.mma_async.sync.aligned.m64n256k16.f32.bf16.bf16 " REGS128 ", %128, %129, 1, 1, 1, 0, 1;\n"
                 : R8(d, 0), R8(d, 8), R8(d, 16), R8(d, 24), R8(d, 32), R8(d, 40), R8(d, 48), R8(d, 56),
                   R8(d, 64), R8(d, 72), R8(d, 80), R8(d, 88), R8(d, 96), R8(d, 104), R8(d, 112), R8(d, 120)
                 : "l"(da), "l"(db));
}

__device__ __forceinline__ int fin_pair(uint32_t fin, int i) {
  const int e0 = fin & 255, ne = ((fin >> 8) & 255) - e0;
  if (i < ne) { const int e = e0 + i; return e < 16 ? e : (e < 30 ? e + 16 : e - 14); }
  return 24 + ((fin >> 16) & 255) + (i - ne);
}
__device__ __forceinline__ int fin_nearly(uint32_t fin) { return ((fin >> 8) & 255) - (fin & 255); }
__device__ __forceinline__ int fin_npairs(uint32_t fin) { return fin_nearly(fin) + (int)(fin >> 24) - (int)((fin >> 16) & 255); }

template <bool PF>
__device__ __forceinline__ void stream(const Params& p, uint32_t sb, uint32_t rank, int cl, int lane) {
  int slot = 0;
  uint32_t ph = 0, n = 0, dep = 1;
  int att_cnt = 0;
  uint32_t st = 0, fb = 0;
  auto begin = [&]() {
    if (PF) {
      if (n >= PF_DIST) dep_wait(sb + B_ISS, n - PF_DIST + 1);
    } else {
      st = sb + slot * SLOT_BYTES; fb = sb + B_FULL + 8 * slot;
      mbar_wait(sb + B_EMPTY + 8 * slot, ph ^ 1);
      mbar_expect_tx(fb, SLOT_BYTES);
    }
  };
  auto end = [&]() {
    ++n;
    if (!PF) {
      asm volatile("st.volatile.shared.u32 [%0], %1;" ::"r"(sb + B_ISS), "r"(n) : "memory");
      if (++slot == NSLOT) { slot = 0; ph ^= 1; }
    }
  };
  bool pf_on = false;
  auto ld2d = [&](uint32_t off, const CUtensorMap* tm, int c0, int c1) {
    if (PF) { if (lane == 0 && pf_on) tma_prefetch_2d(tm, c0, c1); } else tma_load_2d(st + off, tm, c0, c1, fb);
  };
  auto ld2d_mc = [&](uint32_t off, const CUtensorMap* tm, int c0, int c1) {
    if (PF) { if (lane == 0 && pf_on) tma_prefetch_2d(tm, c0, c1); } else tma_load_2d_mc(st + off, tm, c0, c1, fb);
  };
  auto publish = [&]() {
    ++dep;
    if (PF) {
      __syncwarp();
      if (lane == 0) st_release_smem(sb + B_DEP, dep);
    } else {
      dep_wait(sb + B_DEP, dep);
    }
    fence_async_global();
  };
  bool gate_done = false;
  for (int it = 0; it < MAXIT; it++) {
    const uint32_t item = p.sched[cl * MAXIT + it];
    if (item == IT_END) break;
    const int type = item >> 14;
    const int s = item & 7;
    const int m = 2 * s + rank;
    if (PF && (PF_MODE & 8) && cl >= 2) {
      const int j = (cl - 2) * 2 + rank;
      auto pf_cols = [&](const void* w, int pitch, int col0, int ncols) {
        if (lane < 4) bulk_prefetch((const __nv_bfloat16*)w + (size_t)(4 * j + lane) * pitch + col0, ncols * 2);
      };
      if (it == 2) { pf_cols(p.w[1], 4096, 2048, 2048); pf_cols(p.w[2], 4096, 2048, 2048); }
      if (it == 5) { pf_cols(p.w[0], 4096, 2048, 2048); pf_cols(p.w[4], FF, 0, FF); pf_cols(p.w[5], FF, 0, FF); }
      if (type == IT_ATT && att_cnt == 3) {
        if (lane == 0) bulk_prefetch((const uint8_t*)p.w[3] + (size_t)j * 32768, 32768);
        if (lane == 1) bulk_prefetch((const uint8_t*)p.w[6] + (size_t)j * 14336, 14336);
      }
    }
    if (PF && !gate_done && type != IT_KV) {
      if (lane == 0) { flag_wait(&g_flags[FL_G], 256); st_release_smem(sb + B_DEP, 1); }
      __syncwarp();
      gate_done = true;
    }
    if (type == IT_FIN) {
      const int ch = (item >> 3) & 1;
      const uint32_t fin = p.fin[cl];
      const int np = fin_npairs(fin), ne = fin_nearly(fin);
#pragma unroll 1
      for (int i = 0; i < np; i++) {
        if (i == 0 || i == ne) {
          if (PF) {
            const int lim = i < ne ? ne : np;
            if (i + lane < lim) flag_wait(&g_flags[FL_A + fin_pair(fin, i + lane) * 8 + s], 4);
            if (lane == 31) flag_wait(&g_flags[FL_Z], 256);
          }
          publish();
        }
        const int kp = fin_pair(fin, i);
        begin();
        const uint8_t* src = g_a + ((size_t)(m * 46 + kp) << 15);
        if (PF) { if (lane == 0 && (PF_MODE & 2)) bulk_prefetch(src, 32768); } else bulk_load(st, src, 32768, fb);
        end();
        const CUtensorMap* tm = kp >= 32 ? &p.tm[TM_WD] : &p.tm[TM_WO];
        const int krow = (kp >= 32 ? kp - 32 : kp) * 128;
#pragma unroll 1
        for (int k2 = 0; k2 < 2; k2++) {
          begin();
          ld2d_mc(rank * 16384, tm, ch * 256 + rank * 128, krow + k2 * 64);
          ld2d_mc(rank * 16384 + 8192, tm, ch * 256 + rank * 128 + 64, krow + k2 * 64);
          end();
        }
      }
    } else if (type != IT_ATT) {
      const int nb = (item >> 3) & 31;
      const CUtensorMap* tma = type == IT_KV ? &p.tm[TM_C] : &p.tm[TM_X];
      const CUtensorMap* tmb;
      int col;
      if (type == IT_KV) { tmb = (nb & 1) ? &p.tm[TM_WUV] : &p.tm[TM_WUK]; col = (nb >> 1) * 256 + rank * 128; }
      else { tmb = rank ? &p.tm[TM_WU] : &p.tm[TM_WG]; col = nb * 128; }
#pragma unroll 1
      for (int kp = 0; kp < 4; kp++) {
        begin();
        ld2d(0, tma, kp * 128, m * 128);
        ld2d(16384, tma, kp * 128 + 64, m * 128);
        end();
#pragma unroll 1
        for (int k2 = 0; k2 < 2; k2++) {
          begin();
          pf_on = (PF_MODE & 1) && it == 1 && kp * 2 + k2 == s;
          ld2d_mc(rank * 16384, tmb, col, kp * 128 + k2 * 64);
          ld2d_mc(rank * 16384 + 8192, tmb, col + 64, kp * 128 + k2 * 64);
          pf_on = false;
          end();
        }
      }
    } else {
      const int h = (item >> 3) & 31;
      const int lo = 4 * s + rank, hi = 4 * s + 3 - rank;
      const int r0 = (att_cnt & 1) ? hi : lo, r1 = (att_cnt & 1) ? lo : hi;
      att_cnt++;
#pragma unroll 1
      for (int kb = 0; kb < 8; kb++) {
        begin();
        ld2d(0, &p.tm[TM_X64], kb * 64, r0 * 64);
        ld2d(8192, &p.tm[TM_X64], kb * 64, r1 * 64);
        ld2d_mc(16384 + rank * 8192, &p.tm[TM_WQ], h * 128 + rank * 64, kb * 64);
        end();
      }
      if (PF) { if (lane < 16 && (lane & 7) <= s) flag_wait(&g_flags[FL_KV + ((h >> 1) * 2 + (lane >> 3)) * 8 + (lane & 7)], 4); }
      publish();
      const int nbk = 2 * s + 2;
      const uint8_t* kbase = g_kv + ((size_t)h << 19) + rank * 16384;
      const uint8_t* vbase = kbase + ((size_t)NH << 19);
#pragma unroll 1
      for (int i = 0; i < 2 * nbk; i++) {
        const uint8_t* src;
        if (i == 0) src = kbase;
        else if (i == 2 * nbk - 1) src = vbase + ((size_t)(nbk - 1) << 15);
        else if (i & 1) src = kbase + ((size_t)((i + 1) >> 1) << 15);
        else src = vbase + ((size_t)((i >> 1) - 1) << 15);
        begin();
        if (PF) { if (lane == 0 && (PF_MODE & 4) && s == 7) bulk_prefetch(src, 16384); } else bulk_load_mc(st + rank * 16384, src, 16384, fb);
        end();
      }
    }
  }
}

__device__ __forceinline__ void storer(const Params& p, uint32_t sb, uint32_t rank, int cl, int c, int lane) {
  const uint32_t stg = sb + STG_OFF + c * 16384;
  if (blockIdx.x < 128) {
    const int row = blockIdx.x * 16 + c * 8;
    mbar_wait(sb + B_FULL + 8 * (GATE_DELAY - 1), 0);
    if (lane == 0) {
      mbar_expect_tx(sb + B_GATE + 8 * c, 8192);
      bulk_load(stg, p.x + (size_t)row * DM, 8192, sb + B_GATE + 8 * c);
    }
    const uint4* gw = reinterpret_cast<const uint4*>(p.gate_w);
    const uint4 wv0 = __ldg(gw + lane), wv1 = __ldg(gw + 32 + lane);
    mbar_wait(sb + B_GATE + 8 * c, 0);
    float mine = 0.f;
#pragma unroll 2
    for (int r = 0; r < 8; r++) {
      uint4 xv0, xv1;
      asm volatile("ld.shared.v4.u32 {%0,%1,%2,%3}, [%4];" : "=r"(xv0.x), "=r"(xv0.y), "=r"(xv0.z), "=r"(xv0.w) : "r"(stg + r * 1024 + lane * 16));
      asm volatile("ld.shared.v4.u32 {%0,%1,%2,%3}, [%4];" : "=r"(xv1.x), "=r"(xv1.y), "=r"(xv1.z), "=r"(xv1.w) : "r"(stg + r * 1024 + 512 + lane * 16));
      float acc = 0.f;
      auto dot = [&](uint32_t a, uint32_t b) {
        acc = fmaf(__uint_as_float(a << 16), __uint_as_float(b << 16), acc);
        acc = fmaf(__uint_as_float(a & 0xffff0000u), __uint_as_float(b & 0xffff0000u), acc);
      };
      dot(xv0.x, wv0.x); dot(xv0.y, wv0.y); dot(xv0.z, wv0.z); dot(xv0.w, wv0.w);
      dot(xv1.x, wv1.x); dot(xv1.y, wv1.y); dot(xv1.z, wv1.z); dot(xv1.w, wv1.w);
#pragma unroll
      for (int o = 16; o > 0; o >>= 1) acc += __shfl_xor_sync(0xffffffffu, acc, o);
      if (lane == r) mine = acc;
    }
    if (lane < 8) g_gate[row + lane] = 1.0f / (1.0f + __expf(-mine));
    __syncwarp();
    if (lane == 0) { mbar_arrive(sb + B_STGE + 8 * c); red_release(&g_flags[FL_G], 1); }
  } else if (lane == 0) {
    mbar_arrive(sb + B_STGE + 8 * c);
  }
  uint32_t ph = 0;
  int att_cnt = 0;
  for (int it = 0; it < MAXIT; it++) {
    const uint32_t item = p.sched[cl * MAXIT + it];
    if (item == IT_END) break;
    if (it == 3) {
      __syncwarp();
      if (blockIdx.x < 128) {
        uint4* oz = reinterpret_cast<uint4*>(p.out + (size_t)(blockIdx.x * 16 + c * 8) * DM);
#pragma unroll 4
        for (int r = 0; r < 16; r++) oz[r * 32 + lane] = make_uint4(0, 0, 0, 0);
        __syncwarp();
        if (lane == 0) red_release(&g_flags[FL_Z], 1);
      }
    }
    if (lane != 0) continue;
    const int type = item >> 14;
    const int s = item & 7, nb = (item >> 3) & 31;
    const int m = 2 * s + rank;
    if (type == IT_FIN) {
#pragma unroll 1
      for (int rd = 0; rd < 2; rd++) {
        mbar_wait(sb + B_STGF + 8 * c, ph);
        ph ^= 1;
        fence_async_global();
        tma_reduce_add_2d(&p.tm[TM_OUT], (nb & 1) * 256 + rd * 128, m * 128 + c * 64, stg);
        tma_reduce_add_2d(&p.tm[TM_OUT], (nb & 1) * 256 + rd * 128 + 64, m * 128 + c * 64, stg + 8192);
        bulk_commit();
        bulk_wait_read();
        mbar_arrive(sb + B_STGE + 8 * c);
      }
      continue;
    }
    uint8_t* dst;
    int flag, rounds = 1;
    if (type == IT_KV) {
      dst = g_kv + ((size_t)((nb & 1) * NH + (nb >> 1) * 2) << 19) + ((size_t)m << 15) + c * 8192;
      flag = FL_KV + nb * 8 + s;
      rounds = 2;
    } else if (type == IT_UP) {
      dst = g_a + ((size_t)(m * 46 + 32 + nb) << 15) + c * 8192;
      flag = FL_A + (32 + nb) * 8 + s;
    } else {
      const bool is_hi = ((att_cnt & 1) ^ c) != 0;
      att_cnt++;
      const int r = is_hi ? 4 * s + 3 - rank : 4 * s + rank;
      dst = g_a + ((size_t)((r >> 1) * 46 + nb) << 15) + (r & 1) * 8192;
      flag = FL_A + nb * 8 + s;
    }
#pragma unroll 1
    for (int rd = 0; rd < rounds; rd++) {
      mbar_wait(sb + B_STGF + 8 * c, ph);
      ph ^= 1;
      bulk_store(dst, stg, 8192);
      bulk_store(dst + 16384, stg + 8192, 8192);
      bulk_commit();
      bulk_wait_read();
      mbar_arrive(sb + B_STGE + 8 * c);
      dst += (size_t)1 << 19;
    }
    bulk_wait_all();
    red_release(&g_flags[flag], 1);
  }
}

__device__ __forceinline__ void consumer(const Params& p, uint32_t sb, uint32_t rank, int cl, int c, int w, int lane) {
  const uint32_t sb16 = (sb & 0x3FFFF) >> 4;
  const uint32_t stsm_base = sb + STG_OFF + c * 16384 + (w * 16 + (lane & 7) + ((lane >> 3) & 1) * 8) * 128;
  const uint32_t stsm_x = ((lane >> 4) ^ (lane & 7)) << 4;
  uint32_t sph = 0;
  const uint32_t rel = mapa(sb + B_EMPTY, lane & 1);
  const bool rel_p = lane < 2;
  auto release = [&](int slot) { if (rel_p) mbar_arrive_cluster(rel + 8 * slot); };
  auto stage_store = [&](const uint32_t (&pk)[32]) {
    mbar_wait(sb + B_STGE + 8 * c, sph);
    sph ^= 1;
#pragma unroll
    for (int kk = 0; kk < 8; kk++)
      stsm4(stsm_base + (kk >> 2) * 8192 + (stsm_x ^ ((kk & 3) << 5)), pk[4 * kk], pk[4 * kk + 1], pk[4 * kk + 2], pk[4 * kk + 3]);
    fence_async_smem();
    __syncwarp();
    if (lane == 0) mbar_arrive(sb + B_STGF + 8 * c);
  };

  PROF(31, 0); PROFG(31, 1);
  bool gate_ok = false;
  int as = 0;
  uint32_t aph = 0;
  auto adv = [&]() { if (++as == NSLOT) { as = 0; aph ^= 1; } };
  int att_cnt = 0;
  const int rowq = lane >> 2;
  uint32_t P[32];
  bool deferred = false;
#pragma unroll
  for (int i = 0; i < 32; i++) P[i] = 0;
  for (int it = 0; it < MAXIT; it++) {
    const uint32_t item = p.sched[cl * MAXIT + it];
    if (item == IT_END) break;
    const int type = item >> 14;
    const int s = item & 7;
    PROF(it, 0);
    if (type != IT_ATT) {
      const int m = 2 * s + rank;
      const int np = type == IT_FIN ? fin_npairs(p.fin[cl]) : 4;
      float acc[128];
      int sa, sb0, sb1;
      auto kblock = [&](auto init, int aoff, int bslot) {
        const uint32_t da = sb16 + sa * (SLOT_BYTES >> 4) + c * 512 + aoff, db = sb16 + bslot * (SLOT_BYTES >> 4);
        WG_FENCE();
        wgmma_ss_n256<decltype(init)::value>(acc, mk_desc(da, 0, 16), mk_desc(db, 0, 8192));
#pragma unroll
        for (int kk = 1; kk < 4; kk++) wgmma_ss_n256<0>(acc, mk_desc(da, kk * 32, 16), mk_desc(db, kk * 2048, 8192));
        WG_COMMIT();
      };
      sa = as; mbar_wait(sb + B_FULL + 8 * as, aph); adv();
      PROFX(it, 1);
      sb0 = as; mbar_wait(sb + B_FULL + 8 * as, aph); adv();
      PROFX(it, 0);
      kblock(IC<1>(), 0, sb0);
      sb1 = as; mbar_wait(sb + B_FULL + 8 * as, aph); adv();
      kblock(IC<0>(), 1024, sb1);
      if (deferred) { stage_store(P); deferred = false; }
      WG_WAIT(1);
      release(sb0);
#pragma unroll 1
      for (int kp = 1; kp < np; kp++) {
        const int pa = sa, pb = sb1;
        sa = as; mbar_wait(sb + B_FULL + 8 * as, aph); adv();
        sb0 = as; mbar_wait(sb + B_FULL + 8 * as, aph); adv();
        kblock(IC<0>(), 0, sb0);
        WG_WAIT(1);
        release(pa); release(pb);
        sb1 = as; mbar_wait(sb + B_FULL + 8 * as, aph); adv();
        kblock(IC<0>(), 1024, sb1);
        WG_WAIT(1);
        release(sb0);
      }
      float g0 = 0.f, g1 = 0.f;
      if (type == IT_UP) {
        if (!gate_ok) { dep_wait(sb + B_DEP, 1); gate_ok = true; }
        const int row = m * 128 + c * 64 + w * 16 + rowq;
        g0 = 0.5f - 0.5f * __ldcg(&g_gate[row]);
        g1 = 0.5f - 0.5f * __ldcg(&g_gate[row + 8]);
      }
      WG_WAIT(0);
      reg_fence(acc);
      release(sa); release(sb1);
      PROF(it, 1);
      if (type == IT_KV) {
        uint32_t pk[32];
#pragma unroll
        for (int i = 0; i < 32; i++) pk[i] = pack_bf16(acc[2 * i], acc[2 * i + 1]);
        stage_store(pk);
#pragma unroll
        for (int i = 0; i < 32; i++) P[i] = pack_bf16(acc[64 + 2 * i], acc[64 + 2 * i + 1]);
        deferred = true;
      } else if (type == IT_UP) {
        uint32_t pk[32];
#pragma unroll
        for (int i = 0; i < 32; i++) {
          float hv[2];
#pragma unroll
          for (int e = 0; e < 2; e++) {
            const float gt = acc[2 * i + e], up = acc[64 + 2 * i + e];
            const float u = gt * fmaf(gt * gt, 0.044715f * 0.7978845608028654f, 0.7978845608028654f);
            const float hg = gt * up * ((i & 1) ? g1 : g0);
            hv[e] = fmaf(hg, tanh_fast(u), hg);
          }
          pk[i] = pack_bf16(hv[0], hv[1]);
        }
        stage_store(pk);
      } else {
#pragma unroll
        for (int hf = 0; hf < 2; hf++) {
          uint32_t pk[32];
#pragma unroll
          for (int i = 0; i < 32; i++) pk[i] = pack_bf16(acc[hf * 64 + 2 * i], acc[hf * 64 + 2 * i + 1]);
          stage_store(pk);
        }
      }
    } else {
      const bool is_hi = ((att_cnt & 1) ^ c) != 0;
      att_cnt++;
      const int r = is_hi ? 4 * s + 3 - rank : 4 * s + rank;
      const int nb = (r >> 1) + 1;
      float S[64], O[64];
      uint32_t P2[32];
      {
        int prev = as;
        {
          const uint32_t st = sb16 + as * (SLOT_BYTES >> 4);
          mbar_wait(sb + B_FULL + 8 * as, aph);
          PROFX(it, 0);
          WG_FENCE();
          wgmma_ss_n128<1, 1>(S, mk_desc(st + c * 512, 0, 16), mk_desc(st, 16384, 8192));
#pragma unroll
          for (int kk = 1; kk < 4; kk++)
            wgmma_ss_n128<1, 0>(S, mk_desc(st + c * 512, kk * 32, 16), mk_desc(st, 16384 + kk * 2048, 8192));
          WG_COMMIT();
          adv();
        }
#pragma unroll 1
        for (int kb = 1; kb < 8; kb++) {
          const uint32_t st = sb16 + as * (SLOT_BYTES >> 4);
          mbar_wait(sb + B_FULL + 8 * as, aph);
          WG_FENCE();
#pragma unroll
          for (int kk = 0; kk < 4; kk++)
            wgmma_ss_n128<1, 0>(S, mk_desc(st + c * 512, kk * 32, 16), mk_desc(st, 16384 + kk * 2048, 8192));
          WG_COMMIT();
          if (kb == 1 && deferred) { stage_store(P); deferred = false; }
          WG_WAIT(1);
          release(prev);
          prev = as;
          adv();
        }
        mbar_wait(sb + B_STGE + 8 * c, sph);
        WG_WAIT(0);
        reg_fence(S);
        release(prev);
#pragma unroll
        for (int kk = 0; kk < 8; kk++)
          stsm4(stsm_base + (kk >> 2) * 8192 + (stsm_x ^ ((kk & 3) << 5)), pack_bf16(S[8 * kk], S[8 * kk + 1]), pack_bf16(S[8 * kk + 2], S[8 * kk + 3]),
                pack_bf16(S[8 * kk + 4], S[8 * kk + 5]), pack_bf16(S[8 * kk + 6], S[8 * kk + 7]));
        fence_async_smem();
        asm volatile("bar.sync %0, 128;" ::"r"(c + 1) : "memory");
      }
      PROF(it, 1);
      const float cs = 0.08838834764831845f * 1.4426950408889634f;
      float nm0 = 0.f, nm1 = 0.f, l0 = 0.f, l1 = 0.f, s0, s1;
      const float LAZY_T = 256.f;
      const int thr = w * 16 + rowq + (r & 1) * 64 - (lane & 3) * 2;
      const uint32_t q16 = sb16 + ((STG_OFF + c * 16384) >> 4);

      auto issue_qk = [&](int slot) {
        const uint32_t st = sb16 + slot * (SLOT_BYTES >> 4);
        wgmma_ss_n128<0, 1>(S, mk_desc(q16, 0, 16), mk_desc(st, 0, 16));
#pragma unroll
        for (int kk = 1; kk < 8; kk++)
          wgmma_ss_n128<0, 0>(S, mk_desc(q16, (kk >> 2) * 8192 + (kk & 3) * 32, 16), mk_desc(st, (kk >> 2) * 16384 + (kk & 3) * 32, 16));
        WG_COMMIT();
      };
      auto issue_pv = [&](int slot, uint32_t (&Pc)[32]) {
        const uint32_t st = sb16 + slot * (SLOT_BYTES >> 4);
#pragma unroll
        for (int kk = 0; kk < 8; kk++)
          wgmma_rs_n128<1, 0>(O, Pc[4 * kk], Pc[4 * kk + 1], Pc[4 * kk + 2], Pc[4 * kk + 3], mk_desc(st, kk * 2048, 16384));
        WG_COMMIT();
      };
      auto mask = [&]() {
#pragma unroll
        for (int j = 0; j < 16; j++) {
#pragma unroll
          for (int e = 0; e < 2; e++) {
            if (8 * j + e > thr) S[4 * j + e] = -INFINITY;
            if (8 * j + e > thr + 8) S[4 * j + 2 + e] = -INFINITY;
          }
        }
      };
      auto row_max = [&](float& a0, float& a1) {
        float b0, b1;
        a0 = fmaxf(S[0], S[1]); a1 = fmaxf(S[2], S[3]); b0 = fmaxf(S[4], S[5]); b1 = fmaxf(S[6], S[7]);
#pragma unroll
        for (int j = 2; j < 16; j += 2) {
          a0 = fmaxf(a0, fmaxf(S[4 * j], S[4 * j + 1]));
          a1 = fmaxf(a1, fmaxf(S[4 * j + 2], S[4 * j + 3]));
          b0 = fmaxf(b0, fmaxf(S[4 * j + 4], S[4 * j + 5]));
          b1 = fmaxf(b1, fmaxf(S[4 * j + 6], S[4 * j + 7]));
        }
        a0 = fmaxf(a0, b0); a1 = fmaxf(a1, b1);
        a0 = fmaxf(a0, __shfl_xor_sync(0xffffffffu, a0, 1));
        a1 = fmaxf(a1, __shfl_xor_sync(0xffffffffu, a1, 1));
        a0 = fmaxf(a0, __shfl_xor_sync(0xffffffffu, a0, 2));
        a1 = fmaxf(a1, __shfl_xor_sync(0xffffffffu, a1, 2));
        a0 *= cs; a1 *= cs;
      };
      auto exp_pack = [&](uint32_t (&Pn)[32]) {
        s0 = 0.f; s1 = 0.f;
#pragma unroll
        for (int j = 0; j < 16; j++) {
          const float e0 = ex2(fmaf(S[4 * j], cs, nm0)), e1 = ex2(fmaf(S[4 * j + 1], cs, nm0));
          const float e2 = ex2(fmaf(S[4 * j + 2], cs, nm1)), e3 = ex2(fmaf(S[4 * j + 3], cs, nm1));
          s0 += e0 + e1;
          s1 += e2 + e3;
          Pn[2 * j] = pack_bf16(e0, e1);
          Pn[2 * j + 1] = pack_bf16(e2, e3);
        }
      };
      auto body = [&](uint32_t (&Pc)[32], uint32_t (&Pn)[32], bool last) {
        const int ks = as;
        adv();
        const int vs = as;
        reg_fence_u(Pc);
        reg_fence(O);
        WG_FENCE();
        issue_qk(ks);
        mbar_wait(sb + B_FULL + 8 * as, aph);
        adv();
        WG_FENCE();
        issue_pv(vs, Pc);
        WG_WAIT(1);
        reg_fence(S);
        release(ks);
        if (last) mask();
        bool fixed = false;
        while (true) {
          exp_pack(Pn);
          reg_fence_u(Pn);
          mbar_wait(sb + B_FULL + 8 * as, aph);
          WG_WAIT(0);
          reg_fence(O);
          reg_fence_u(Pc);
          if (fixed || !__any_sync(0xffffffffu, !(s0 <= LAZY_T && s1 <= LAZY_T))) break;
          float a0, a1;
          row_max(a0, a1);
          a0 = fminf(-a0, nm0); a1 = fminf(-a1, nm1);
          const float sc0 = ex2(a0 - nm0), sc1 = ex2(a1 - nm1);
          nm0 = a0; nm1 = a1;
          l0 *= sc0; l1 *= sc1;
#pragma unroll
          for (int i = 0; i < 16; i++) {
            O[4 * i] *= sc0; O[4 * i + 1] *= sc0; O[4 * i + 2] *= sc1; O[4 * i + 3] *= sc1;
          }
          fixed = true;
        }
        release(vs);
        l0 += s0; l1 += s1;
      };

      mbar_wait(sb + B_FULL + 8 * as, aph);
      WG_FENCE();
      issue_qk(as);
#pragma unroll
      for (int i = 0; i < 64; i++) O[i] = 0.f;
      WG_WAIT(0);
      reg_fence(S);
      release(as);
      adv();
      PROFX(it, 1);
      if (nb == 1) mask();
      row_max(nm0, nm1);
      nm0 = -nm0; nm1 = -nm1;
      exp_pack(P);
      l0 = s0; l1 = s1;
      mbar_wait(sb + B_FULL + 8 * as, aph);
      int j = 1;
      PROFX(it, 2);
#pragma unroll 1
      for (; j + 1 < nb; j += 2) {
        body(P, P2, false);
        body(P2, P, j + 2 == nb);
      }
      if (j < nb) {
        body(P, P2, true);
#pragma unroll
        for (int i = 0; i < 32; i++) P[i] = P2[i];
      }
      PROFX(it, 3);
      if (!is_hi) {
        release(as);
        adv();
        mbar_wait(sb + B_FULL + 8 * as, aph);
      }
      reg_fence_u(P);
      reg_fence(O);
      WG_FENCE();
      issue_pv(as, P);
      if (!gate_ok) { dep_wait(sb + B_DEP, 1); gate_ok = true; }
      const int qrow = r * 64 + w * 16 + rowq;
      const float gt0 = __ldcg(&g_gate[qrow]), gt1 = __ldcg(&g_gate[qrow + 8]);
      l0 += __shfl_xor_sync(0xffffffffu, l0, 1); l1 += __shfl_xor_sync(0xffffffffu, l1, 1);
      l0 += __shfl_xor_sync(0xffffffffu, l0, 2); l1 += __shfl_xor_sync(0xffffffffu, l1, 2);
      const float f0 = __fdividef(gt0, l0), f1 = __fdividef(gt1, l1);
      WG_WAIT(0);
      reg_fence(O);
      reg_fence_u(P);
      release(as);
      adv();
      if (!is_hi) {
        mbar_wait(sb + B_FULL + 8 * as, aph);
        release(as);
        adv();
      }
      PROF(it, 2);
#pragma unroll
      for (int i = 0; i < 16; i++) {
        P[2 * i] = pack_bf16(O[4 * i] * f0, O[4 * i + 1] * f0);
        P[2 * i + 1] = pack_bf16(O[4 * i + 2] * f1, O[4 * i + 3] * f1);
      }
      stage_store(P);
    }
    PROF(it, 3);
  }
  if (deferred) stage_store(P);
  PROF(30, 0); PROFG(30, 1);
}

__global__ void __cluster_dims__(2, 1, 1) __launch_bounds__(384, 1) mega_kernel(const __grid_constant__ Params p) {
  extern __shared__ uint8_t smem_raw[];
  const uint32_t sb = (smem_u32(smem_raw) + 1023) & ~1023u;
  const int warp = __shfl_sync(0xffffffffu, threadIdx.x >> 5, 0), lane = threadIdx.x & 31;
  uint32_t rank;
  asm volatile("mov.u32 %0, %%cluster_ctarank;" : "=r"(rank));
  const int cl = blockIdx.x >> 1;
  if ((PF_MODE & 32) && warp == 2 && lane < TM_COUNT)
    asm volatile("prefetch.tensormap [%0];" ::"l"(&p.tm[lane]) : "memory");
  if ((PF_MODE & 16) && warp == 1 && blockIdx.x < 128) {
    const int j = blockIdx.x;
    const int r4 = 4 * j + (lane & 3), g = lane >> 2;
    if (g == 0) bulk_prefetch((const uint8_t*)p.c + (size_t)r4 * 4096, 4096);
    if (g == 1) bulk_prefetch((const __nv_bfloat16*)p.w[1] + (size_t)r4 * 4096, 2048);
    if (g == 2) bulk_prefetch((const __nv_bfloat16*)p.w[2] + (size_t)r4 * 4096, 2048);
    if (g == 3) bulk_prefetch((const __nv_bfloat16*)p.w[1] + (size_t)r4 * 4096 + 1024, 2048);
    if (g == 4) bulk_prefetch((const __nv_bfloat16*)p.w[2] + (size_t)r4 * 4096 + 1024, 2048);
    if (g == 5) bulk_prefetch((const __nv_bfloat16*)p.w[0] + (size_t)r4 * 4096, 4096);
  }
  if (threadIdx.x == 0) {
    for (int i = 0; i < NSLOT; i++) { mbar_init(sb + B_FULL + 8 * i, 1); mbar_init(sb + B_EMPTY + 8 * i, 16); }
    for (int i = 0; i < 2; i++) { mbar_init(sb + B_STGF + 8 * i, 4); mbar_init(sb + B_STGE + 8 * i, 1); mbar_init(sb + B_GATE + 8 * i, 1); }
    st_release_smem(sb + B_DEP, 0);
    st_release_smem(sb + B_ISS, 0);
    asm volatile("fence.mbarrier_init.release.cluster;" ::: "memory");
  }
  __syncthreads();
  cluster_sync();
  if (warp < 4) {
    asm volatile("setmaxnreg.dec.sync.aligned.u32 40;");
    if (warp == 0) { if (lane == 0) stream<false>(p, sb, rank, cl, 0); }
    else if (warp == 1) {
      stream<true>(p, sb, rank, cl, lane);
      unsigned t = 0;
      if (lane == 0) { __threadfence(); t = atomicAdd(&g_flags[FL_TICKET], 1); }
      t = __shfl_sync(0xffffffffu, t, 0);
      if (t == gridDim.x - 1) {
        __threadfence();
        for (int i = lane; i < FL_TOTAL; i += 32) g_flags[i] = 0;
      }
    }
    else storer(p, sb, rank, cl, warp - 2, lane);
    __syncwarp();
    cluster_sync_relaxed();
  } else {
    asm volatile("setmaxnreg.inc.sync.aligned.u32 232;");
    consumer(p, sb, rank, cl, (warp >> 2) - 1, warp & 3, lane);
    cluster_sync_relaxed();
  }
}

typedef CUresult (*EncodeFn)(CUtensorMap*, CUtensorMapDataType, cuuint32_t, void*, const cuuint64_t*, const cuuint64_t*,
                             const cuuint32_t*, const cuuint32_t*, CUtensorMapInterleave, CUtensorMapSwizzle,
                             CUtensorMapL2promotion, CUtensorMapFloatOOBfill);

void make_map(EncodeFn enc, CUtensorMap* tm, const void* ptr, int rows, int cols, int box_rows) {
  cuuint64_t gd[2] = {(cuuint64_t)cols, (cuuint64_t)rows};
  cuuint64_t gs[1] = {(cuuint64_t)cols * 2};
  cuuint32_t box[2] = {64, (cuuint32_t)box_rows};
  cuuint32_t es[2] = {1, 1};
  enc(tm, CU_TENSOR_MAP_DATA_TYPE_BFLOAT16, 2, const_cast<void*>(ptr), gd, gs, box, es, CU_TENSOR_MAP_INTERLEAVE_NONE,
      CU_TENSOR_MAP_SWIZZLE_128B, CU_TENSOR_MAP_L2_PROMOTION_L2_256B, CU_TENSOR_MAP_FLOAT_OOB_FILL_NONE);
}

void build_sched(uint16_t* sched, uint32_t* fin) {
  const double C_KV = 10500, C_UP = 11100, C_ATT0 = 10000, C_ATTS = 4350, C_PAIR = 2250;
  const int AUX_UP = 14;
  int cnt[MAXCL];
  double t[MAXCL];
  for (int c = 0; c < MAXCL; c++) { cnt[c] = 0; t[c] = 0; fin[c] = 0; }
  auto push = [&](int c, int item, double cost) { sched[c * MAXIT + cnt[c]++] = (uint16_t)item; t[c] += cost; };
  auto push_kv = [&](int g) { for (int j = 0; j < 64; j++) push(2 + j, (IT_KV << 14) | (g * 64 + j), C_KV); };
  auto push_up = [&]() {
    int u = 0;
    for (; u < 112 - 2 * AUX_UP; u++) {
      const int j = u < 64 ? u : ((u - 64) * 4 + (u - 64) / 16) & 63;
      push(2 + j, (IT_UP << 14) | u, C_UP);
    }
    for (; u < 112; u++) push(u & 1, (IT_UP << 14) | u, C_UP);
  };
  int sv[4][64];
  {
    bool heavy[64];
    for (int j = 0; j < 64; j++) heavy[j] = false;
    for (int u = 64; u < 112 - 2 * AUX_UP; u++) heavy[((u - 64) * 4 + (u - 64) / 16) & 63] = true;
    for (int j = 0; j < 64; j++) { sv[0][j] = 7 - (j & 7); sv[1][j] = j & 7; sv[2][j] = 7 - (j & 7); sv[3][j] = j & 7; }
    auto cost = [&](int j) { return (heavy[j] ? C_UP : 0.0) + C_ATTS * (sv[2][j] + sv[3][j]); };
    for (int iter = 0; iter < 200; iter++) {
      bool any = false;
      for (int a = 0; a < 64; a++)
        for (int b = 0; b < 64; b++)
          for (int r = 2; r < 4; r++) {
            const double ca = cost(a), cb = cost(b);
            const int t0 = sv[r][a]; sv[r][a] = sv[r][b]; sv[r][b] = t0;
            const double na = cost(a), nb2 = cost(b);
            if (na * na + nb2 * nb2 < ca * ca + cb * cb - 1.0) any = true;
            else { const int t1 = sv[r][a]; sv[r][a] = sv[r][b]; sv[r][b] = t1; }
          }
      if (!any) break;
    }
  }
  auto push_att = [&](int rnd) {
    int used[8] = {0, 0, 0, 0, 0, 0, 0, 0};
    for (int c = 0; c < 64; c++) {
      const int s = sv[rnd][c], h = rnd * 8 + used[s]++;
      push(c + 2, (IT_ATT << 14) | (h << 3) | s, C_ATT0 + C_ATTS * s);
    }
  };
  push_kv(0); push_kv(1);
  push_att(0); push_kv(2); push_kv(3); push_att(1);
  push_att(2); push_up(); push_att(3);
  double load[16];
  for (int g = 0; g < 16; g++) { load[g] = 0; for (int q = 0; q < 4; q++) load[g] += t[2 + 4 * g + q]; }
  int aux_tile[2] = {-1, -1};
  for (int a = 0; a < 2; a++) {
    int best = -1;
    for (int g = 0; g < 16; g++) if (g != aux_tile[0] && (best < 0 || load[g] > load[best])) best = g;
    aux_tile[a] = best;
  }
  for (int g = 0; g < 16; g++) {
    int members[5], nm = 0, ne[5];
    for (int q = 0; q < 4; q++) members[nm++] = 2 + 4 * g + q;
    for (int a = 0; a < 2; a++) if (aux_tile[a] == g) members[nm++] = a;
    double e[5];
    for (int i = 0; i < nm; i++) { ne[i] = 0; e[i] = t[members[i]] + (i < 4 ? 2 * C_PAIR : 0); }
    for (int k = 0; k < 38; k++) {
      int b = 0;
      for (int i = 1; i < nm; i++) if (e[i] < e[b]) b = i;
      ne[b]++; e[b] += C_PAIR;
    }
    int e0 = 0;
    for (int i = 0; i < nm; i++) {
      const int l0 = i < 4 ? 2 * i : 0, l1 = i < 4 ? 2 * i + 2 : 0;
      fin[members[i]] = e0 | ((e0 + ne[i]) << 8) | (l0 << 16) | (l1 << 24);
      e0 += ne[i];
      if (ne[i] + l1 - l0 > 0) push(members[i], (IT_FIN << 14) | ((g & 1) << 3) | (g >> 1), 0);
    }
  }
  for (int c = 0; c < MAXCL; c++)
    for (int i = cnt[c]; i < MAXIT; i++) sched[c * MAXIT + i] = IT_END;
}

}

extern "C" void kernel_launch(void* const* d_in, const int* in_sizes, int n_in, void* d_out, int out_size) {
  (void)in_sizes; (void)n_in; (void)out_size;
  static Params p;
  static bool init = false;
  static const void* key[12];
  bool same = init;
  for (int i = 0; i < 11 && same; i++) same = key[i] == d_in[i];
  same = same && key[11] == d_out;
  if (!same) {
    EncodeFn enc = nullptr;
    cudaDriverEntryPointQueryResult qr;
    cudaGetDriverEntryPoint("cuTensorMapEncodeTiled", (void**)&enc, cudaEnableDefault, &qr);
    make_map(enc, &p.tm[TM_X64], d_in[0], SEQ, DM, 64);
    make_map(enc, &p.tm[TM_X], d_in[0], SEQ, DM, 128);
    make_map(enc, &p.tm[TM_C], d_in[1], SEQ, DM, 128);
    make_map(enc, &p.tm[TM_WQ], d_in[2], DM, NH * 128, 64);
    make_map(enc, &p.tm[TM_WUK], d_in[3], DM, NH * 128, 64);
    make_map(enc, &p.tm[TM_WUV], d_in[4], DM, NH * 128, 64);
    make_map(enc, &p.tm[TM_WO], d_in[5], NH * 128, DM, 64);
    make_map(enc, &p.tm[TM_WG], d_in[7], DM, FF, 64);
    make_map(enc, &p.tm[TM_WU], d_in[8], DM, FF, 64);
    make_map(enc, &p.tm[TM_WD], d_in[9], FF, DM, 64);
    make_map(enc, &p.tm[TM_OUT], d_out, SEQ, DM, 64);
    p.x = (const __nv_bfloat16*)d_in[0];
    p.c = (const __nv_bfloat16*)d_in[1];
    p.gate_w = (const __nv_bfloat16*)d_in[10];
    p.out = (__nv_bfloat16*)d_out;
    p.w[0] = d_in[2]; p.w[1] = d_in[3]; p.w[2] = d_in[4]; p.w[3] = d_in[5]; p.w[4] = d_in[7]; p.w[5] = d_in[8]; p.w[6] = d_in[9];
    build_sched(p.sched, p.fin);
    cudaFuncSetAttribute(mega_kernel, cudaFuncAttributeMaxDynamicSharedMemorySize, SMEM_BYTES);
    for (int i = 0; i < 11; i++) key[i] = d_in[i];
    key[11] = d_out;
    init = true;
  }
  mega_kernel<<<2 * MAXCL, 384, SMEM_BYTES>>>(p);
}
```

```cpp
#include <cuda_runtime.h>
#include <cuda_bf16.h>
#include <cuda.h>
#include <stdint.h>

namespace {

constexpr int SEQ = 2048, DM = 512, NH = 32, FF = 1792;
constexpr int MAXCL = 66;
constexpr int MAXIT = 20;
constexpr int AUX_UP = 15;

constexpr int NSLOT = 6, SLOT_BYTES = 32768;
constexpr int RING_BYTES = NSLOT * SLOT_BYTES;
constexpr int STG_OFF = RING_BYTES;
constexpr int BAR_OFF = STG_OFF + 32768;
constexpr int B_FULL = BAR_OFF, B_EMPTY = B_FULL + 8 * NSLOT;
constexpr int B_EMPTY1 = B_EMPTY + 8 * NSLOT, B_FULL1 = B_EMPTY1 + 8 * NSLOT;
constexpr int B_STGF = B_FULL1 + 8 * NSLOT, B_STGE = B_STGF + 16;
constexpr int B_GATE = B_STGE + 16;
constexpr int B_DEP = B_GATE + 16;
constexpr int B_ISS = B_DEP + 4;
constexpr int B_FINQ = B_ISS + 4;
constexpr int SMEM_BYTES = BAR_OFF + 512 + 1024;
constexpr int SCOUT_DIST = 24;
constexpr int FIN_LEAD = 8;
constexpr uint32_t FQ_VALID = 0x100, FQ_END = 0x200;

constexpr int FL_KV = 0;
constexpr int FL_A = FL_KV + 256;
constexpr int FL_FC = FL_A + 46 * 8;
constexpr int FL_FT = FL_FC + 16;
constexpr int FL_G = FL_FT + 1;
constexpr int FL_Z = FL_G + 1;
constexpr int FL_TICKET = FL_Z + 1;
constexpr int FL_TOTAL = FL_TICKET + 1;

enum { TM_X64 = 0, TM_X, TM_C, TM_WQ, TM_WUK, TM_WUV, TM_WO, TM_WG, TM_WU, TM_WD, TM_OUT, TM_COUNT };
enum { IT_KV = 0, IT_UP = 1, IT_ATT = 2, IT_FIN = 3 };

struct Params {
  CUtensorMap tm[TM_COUNT];
  const __nv_bfloat16* x;
  const __nv_bfloat16* gate_w;
  __nv_bfloat16* out;
  uint16_t sched[MAXCL * MAXIT];
};

__device__ __align__(1024) uint8_t g_kv[2 * NH * 16 * 32768];
__device__ __align__(1024) uint8_t g_a[16 * 92 * 16384];
__device__ float g_gate[SEQ];
__device__ unsigned g_flags[FL_TOTAL];

__device__ __forceinline__ uint32_t smem_u32(const void* p) { return (uint32_t)__cvta_generic_to_shared(p); }
__device__ __forceinline__ int lane_id() {
  int l;
  asm volatile("mov.u32 %0, %%laneid;" : "=r"(l));
  return l;
}
__device__ __forceinline__ void mbar_init(uint32_t bar, uint32_t cnt) {
  asm volatile("mbarrier.init.shared::cta.b64 [%0], %1;" ::"r"(bar), "r"(cnt));
}
__device__ __forceinline__ void mbar_expect_tx(uint32_t bar, uint32_t bytes) {
  asm volatile("mbarrier.arrive.expect_tx.shared::cta.b64 _, [%0], %1;" ::"r"(bar), "r"(bytes) : "memory");
}
#define ELECT "{\n.reg .pred el;\nelect.sync _|el, 0xffffffff;\n@el "
__device__ __forceinline__ void mbar_expect_tx_el(uint32_t bar, uint32_t bytes) {
  asm volatile(ELECT "mbarrier.arrive.expect_tx.shared::cta.b64 _, [%0], %1;\n}" ::"r"(bar), "r"(bytes) : "memory");
}
__device__ __forceinline__ uint32_t mapa(uint32_t addr, uint32_t cta) {
  uint32_t r;
  asm("mapa.shared::cluster.u32 %0, %1, %2;" : "=r"(r) : "r"(addr), "r"(cta));
  return r;
}
__device__ __forceinline__ void mbar_arrive_cluster(uint32_t cbar) {
  asm volatile("mbarrier.arrive.shared::cluster.b64 _, [%0];" ::"r"(cbar) : "memory");
}
__device__ __forceinline__ bool mbar_test(uint32_t bar, uint32_t parity) {
  uint32_t ok;
  asm volatile("{\n.reg .pred p;\nmbarrier.test_wait.parity.shared::cta.b64 p, [%1], %2;\nselp.u32 %0, 1, 0, p;\n}"
               : "=r"(ok) : "r"(bar), "r"(parity) : "memory");
  return ok != 0;
}
__device__ __forceinline__ void mbar_wait_b(uint32_t bar, uint32_t parity, int& budget) {
  uint32_t ok;
  asm volatile("{\n.reg .pred p;\nmbarrier.try_wait.parity.shared::cta.b64 p, [%1], %2;\nselp.u32 %0, 1, 0, p;\n}"
               : "=r"(ok) : "r"(bar), "r"(parity) : "memory");
  if (ok) return;
  asm volatile("{\n.reg .pred p, q;\n"
               "WAIT_LOOP:\n"
               "mbarrier.try_wait.parity.shared::cta.b64 p, [%1], %2;\n"
               "@!p sub.s32 %0, %0, 1;\n"
               "setp.gt.and.s32 q, %0, 0, !p;\n"
               "@q bra WAIT_LOOP;\n}"
               : "+r"(budget) : "r"(bar), "r"(parity) : "memory");
}
#define mbar_wait(bar, parity) mbar_wait_b(bar, parity, budget)
constexpr int WAIT_BUDGET = 1 << 20;
__device__ __forceinline__ void tma_load_2d_el(uint32_t dst, const CUtensorMap* tm, int c0, int c1, uint32_t bar) {
  asm volatile(ELECT "cp.async.bulk.tensor.2d.shared::cluster.global.mbarrier::complete_tx::bytes [%0], [%1, {%3, %4}], [%2];\n}"
               ::"r"(dst), "l"(tm), "r"(bar), "r"(c0), "r"(c1) : "memory");
}
__device__ __forceinline__ void tma_load_2d_mc_el(uint32_t dst, const CUtensorMap* tm, int c0, int c1, uint32_t bar) {
  asm volatile(ELECT "cp.async.bulk.tensor.2d.shared::cluster.global.mbarrier::complete_tx::bytes.multicast::cluster [%0], [%1, {%3, %4}], [%2], %5;\n}"
               ::"r"(dst), "l"(tm), "r"(bar), "r"(c0), "r"(c1), "h"((uint16_t)3) : "memory");
}
__device__ __forceinline__ void bulk_load(uint32_t dst, const void* src, uint32_t bytes, uint32_t bar) {
  asm volatile("cp.async.bulk.shared::cluster.global.mbarrier::complete_tx::bytes [%0], [%1], %2, [%3];"
               ::"r"(dst), "l"(src), "r"(bytes), "r"(bar) : "memory");
}
__device__ __forceinline__ void bulk_load_el(uint32_t dst, const void* src, uint32_t bytes, uint32_t bar) {
  asm volatile(ELECT "cp.async.bulk.shared::cluster.global.mbarrier::complete_tx::bytes [%0], [%1], %2, [%3];\n}"
               ::"r"(dst), "l"(src), "r"(bytes), "r"(bar) : "memory");
}
__device__ __forceinline__ void bulk_load_mc_el(uint32_t dst, const void* src, uint32_t bytes, uint32_t bar) {
  asm volatile(ELECT "cp.async.bulk.shared::cluster.global.mbarrier::complete_tx::bytes.multicast::cluster [%0], [%1], %2, [%3], %4;\n}"
               ::"r"(dst), "l"(src), "r"(bytes), "r"(bar), "h"((uint16_t)3) : "memory");
}
__device__ __forceinline__ void bulk_store(void* dst, uint32_t src, uint32_t bytes) {
  asm volatile("cp.async.bulk.global.shared::cta.bulk_group [%0], [%1], %2;" ::"l"(dst), "r"(src), "r"(bytes) : "memory");
}
__device__ __forceinline__ void tma_reduce_add_2d(const CUtensorMap* tm, int c0, int c1, uint32_t src) {
  asm volatile("cp.reduce.async.bulk.tensor.2d.global.shared::cta.add.tile.bulk_group [%0, {%2, %3}], [%1];"
               ::"l"(tm), "r"(src), "r"(c0), "r"(c1) : "memory");
}
__device__ __forceinline__ void bulk_commit() { asm volatile("cp.async.bulk.commit_group;" ::: "memory"); }
__device__ __forceinline__ void bulk_wait_read() { asm volatile("cp.async.bulk.wait_group.read 0;" ::: "memory"); }
__device__ __forceinline__ void bulk_wait_all() { asm volatile("cp.async.bulk.wait_group 0;" ::: "memory"); }
__device__ __forceinline__ void fence_async_smem() { asm volatile("fence.proxy.async.shared::cta;" ::: "memory"); }
__device__ __forceinline__ void fence_async_global() { asm volatile("fence.proxy.async.global;" ::: "memory"); }
__device__ __forceinline__ void mbar_arrive(uint32_t bar) {
  asm volatile("mbarrier.arrive.shared::cta.b64 _, [%0];" ::"r"(bar) : "memory");
}
__device__ __forceinline__ void mbar_arrive_el(uint32_t bar) {
  asm volatile(ELECT "mbarrier.arrive.shared::cta.b64 _, [%0];\n}" ::"r"(bar) : "memory");
}
__device__ __forceinline__ void st_release_smem(uint32_t addr, uint32_t v) {
  asm volatile("st.release.cta.shared.u32 [%0], %1;" ::"r"(addr), "r"(v) : "memory");
}
__device__ __forceinline__ uint32_t ld_acquire_smem(uint32_t addr) {
  uint32_t v;
  asm volatile("ld.acquire.cta.shared.u32 %0, [%1];" : "=r"(v) : "r"(addr) : "memory");
  return v;
}
__device__ __forceinline__ void red_release(unsigned* p, unsigned v) {
  asm volatile("red.release.gpu.global.add.u32 [%0], %1;" ::"l"(p), "r"(v) : "memory");
}
__device__ __forceinline__ unsigned ld_acquire(const unsigned* p) {
  unsigned v;
  asm volatile("ld.acquire.gpu.global.u32 %0, [%1];" : "=r"(v) : "l"(p) : "memory");
  return v;
}
__device__ __forceinline__ void flag_wait_b(const unsigned* p, unsigned target, int& budget) {
  while (ld_acquire(p) < target) {
    __nanosleep(100);
    if (--budget < 0) break;
  }
}
#define flag_wait(p, target) flag_wait_b(p, target, budget)
__device__ __forceinline__ void dep_wait_b(uint32_t addr, uint32_t target, int& budget, unsigned ns = 100) {
  while (ld_acquire_smem(addr) < target) {
    __nanosleep(ns);
    if (--budget < 0) break;
  }
}
#define dep_wait(addr, target) dep_wait_b(addr, target, budget)
template <bool ACQ>
__device__ __forceinline__ uint32_t finq_wait_b(uint32_t addr, int& budget) {
  uint32_t v;
  while (true) {
    if (ACQ) asm volatile("ld.acquire.cluster.shared::cta.u32 %0, [%1];" : "=r"(v) : "r"(addr) : "memory");
    else asm volatile("ld.volatile.shared.u32 %0, [%1];" : "=r"(v) : "r"(addr) : "memory");
    if (v != 0) break;
    __nanosleep(64);
    if (--budget < 0) { v = FQ_END; break; }
  }
  return v;
}
#define finq_wait(addr) finq_wait_b<false>(addr, budget)
__device__ __forceinline__ void cluster_arrive_release() { asm volatile("barrier.cluster.arrive.release.aligned;" ::: "memory"); }
__device__ __forceinline__ void cluster_arrive_relaxed() { asm volatile("barrier.cluster.arrive.relaxed.aligned;" ::: "memory"); }
__device__ __forceinline__ void cluster_wait() { asm volatile("barrier.cluster.wait.acquire.aligned;" ::: "memory"); }
__device__ __forceinline__ void cluster_sync_relaxed() {
  asm volatile("barrier.cluster.arrive.relaxed.aligned;\nbarrier.cluster.wait.aligned;" ::: "memory");
}
__device__ __forceinline__ float ex2(float x) {
  float y;
  asm("ex2.approx.ftz.f32 %0, %1;" : "=f"(y) : "f"(x));
  return y;
}
__device__ __forceinline__ float tanh_fast(float x) {
  float y;
  asm("tanh.approx.f32 %0, %1;" : "=f"(y) : "f"(x));
  return y;
}
__device__ __forceinline__ uint32_t pack_bf16(float lo, float hi) {
  uint32_t r;
  asm("cvt.rn.bf16x2.f32 %0, %1, %2;" : "=r"(r) : "f"(hi), "f"(lo));
  return r;
}
__device__ __forceinline__ void stsm4(uint32_t addr, uint32_t a, uint32_t b, uint32_t c, uint32_t d) {
  asm volatile("stmatrix.sync.aligned.m8n8.x4.shared.b16 [%0], {%1, %2, %3, %4};" ::"r"(addr), "r"(a), "r"(b), "r"(c), "r"(d) : "memory");
}

__device__ __forceinline__ uint64_t mk_desc(uint32_t a16, uint32_t off, uint32_t lbo) {
  uint32_t lo = a16 + ((off >> 4) | ((lbo >> 4) << 16));
  uint32_t hi = (1024 >> 4) | (1u << 30);
  return ((uint64_t)hi << 32) | lo;
}

#define WG_FENCE() asm volatile("wgmma.fence.sync.aligned;" ::: "memory")
#define WG_COMMIT() asm volatile("wgmma.commit_group.sync.aligned;" ::: "memory")
#define WG_WAIT(n) asm volatile("wgmma.wait_group.sync.aligned %0;" ::"n"(n) : "memory")
#define R8(d, b) "+f"(d[b + 0]), "+f"(d[b + 1]), "+f"(d[b + 2]), "+f"(d[b + 3]), "+f"(d[b + 4]), "+f"(d[b + 5]), "+f"(d[b + 6]), "+f"(d[b + 7])
#define W8(d, b) "=f"(d[b + 0]), "=f"(d[b + 1]), "=f"(d[b + 2]), "=f"(d[b + 3]), "=f"(d[b + 4]), "=f"(d[b + 5]), "=f"(d[b + 6]), "=f"(d[b + 7])
#define REGS128 "{%0,%1,%2,%3,%4,%5,%6,%7,%8,%9,%10,%11,%12,%13,%14,%15,%16,%17,%18,%19,%20,%21,%22,%23,%24,%25,%26,%27,%28,%29,%30,%31," \
               "%32,%33,%34,%35,%36,%37,%38,%39,%40,%41,%42,%43,%44,%45,%46,%47,%48,%49,%50,%51,%52,%53,%54,%55,%56,%57,%58,%59,%60,%61,%62,%63," \
               "%64,%65,%66,%67,%68,%69,%70,%71,%72,%73,%74,%75,%76,%77,%78,%79,%80,%81,%82,%83,%84,%85,%86,%87,%88,%89,%90,%91,%92,%93,%94,%95," \
               "%96,%97,%98,%99,%100,%101,%102,%103,%104,%105,%106,%107,%108,%109,%110,%111,%112,%113,%114,%115,%116,%117,%118,%119,%120,%121,%122,%123,%124,%125,%126,%127}"
#define REGS64 "{%0,%1,%2,%3,%4,%5,%6,%7,%8,%9,%10,%11,%12,%13,%14,%15,%16,%17,%18,%19,%20,%21,%22,%23,%24,%25,%26,%27,%28,%29,%30,%31," \
               "%32,%33,%34,%35,%36,%37,%38,%39,%40,%41,%42,%43,%44,%45,%46,%47,%48,%49,%50,%51,%52,%53,%54,%55,%56,%57,%58,%59,%60,%61,%62,%63}"

template <int V> struct IC { static constexpr int value = V; };
template <int N>
__device__ __forceinline__ void reg_fence(float (&d)[N]) {
#pragma unroll
  for (int i = 0; i < N; i++) asm volatile("" : "+f"(d[i])::"memory");
}
template <int N>
__device__ __forceinline__ void reg_fence_u(uint32_t (&d)[N]) {
#pragma unroll
  for (int i = 0; i < N; i++) asm volatile("" : "+r"(d[i])::"memory");
}

template <int TB, int INIT>
__device__ __forceinline__ void wgmma_ss_n128(float (&d)[64], uint64_t da, uint64_t db) {
  if (INIT == 2)
    asm volatile("wgmma.mma_async.sync.aligned.m64n128k16.f32.bf16.bf16 " REGS64 ", %64, %65, 0, 1, 1, 0, %66;\n"
                 : R8(d, 0), R8(d, 8), R8(d, 16), R8(d, 24), R8(d, 32), R8(d, 40), R8(d, 48), R8(d, 56)
                 : "l"(da), "l"(db), "n"(TB));
  else if (INIT)
    asm volatile("wgmma.mma_async.sync.aligned.m64n128k16.f32.bf16.bf16 " REGS64 ", %64, %65, 0, 1, 1, 0, %66;\n"
                 : W8(d, 0), W8(d, 8), W8(d, 16), W8(d, 24), W8(d, 32), W8(d, 40), W8(d, 48), W8(d, 56)
                 : "l"(da), "l"(db), "n"(TB));
  else
    asm volatile("wgmma.mma_async.sync.aligned.m64n128k16.f32.bf16.bf16 " REGS64 ", %64, %65, 1, 1, 1, 0, %66;\n"
                 : R8(d, 0), R8(d, 8), R8(d, 16), R8(d, 24), R8(d, 32), R8(d, 40), R8(d, 48), R8(d, 56)
                 : "l"(da), "l"(db), "n"(TB));
}
template <int TB, int INIT>
__device__ __forceinline__ void wgmma_rs_n128(float (&d)[64], uint32_t a0, uint32_t a1, uint32_t a2, uint32_t a3, uint64_t db) {
  if (INIT == 2)
    asm volatile("wgmma.mma_async.sync.aligned.m64n128k16.f32.bf16.bf16 " REGS64 ", {%64,%65,%66,%67}, %68, 0, 1, 1, %69;\n"
                 : R8(d, 0), R8(d, 8), R8(d, 16), R8(d, 24), R8(d, 32), R8(d, 40), R8(d, 48), R8(d, 56)
                 : "r"(a0), "r"(a1), "r"(a2), "r"(a3), "l"(db), "n"(TB));
  else if (INIT)
    asm volatile("wgmma.mma_async.sync.aligned.m64n128k16.f32.bf16.bf16 " REGS64 ", {%64,%65,%66,%67}, %68, 0, 1, 1, %69;\n"
                 : W8(d, 0), W8(d, 8), W8(d, 16), W8(d, 24), W8(d, 32), W8(d, 40), W8(d, 48), W8(d, 56)
                 : "r"(a0), "r"(a1), "r"(a2), "r"(a3), "l"(db), "n"(TB));
  else
    asm volatile("wgmma.mma_async.sync.aligned.m64n128k16.f32.bf16.bf16 " REGS64 ", {%64,%65,%66,%67}, %68, 1, 1, 1, %69;\n"
                 : R8(d, 0), R8(d, 8), R8(d, 16), R8(d, 24), R8(d, 32), R8(d, 40), R8(d, 48), R8(d, 56)
                 : "r"(a0), "r"(a1), "r"(a2), "r"(a3), "l"(db), "n"(TB));
}
template <int INIT>
__device__ __forceinline__ void wgmma_ss_n256(float (&d)[128], uint64_t da, uint64_t db) {
  if (INIT)
    asm volatile("wgmma.mma_async.sync.aligned.m64n256k16.f32.bf16.bf16 " REGS128 ", %128, %129, 0, 1, 1, 0, 1;\n"
                 : W8(d, 0), W8(d, 8), W8(d, 16), W8(d, 24), W8(d, 32), W8(d, 40), W8(d, 48), W8(d, 56),
                   W8(d, 64), W8(d, 72), W8(d, 80), W8(d, 88), W8(d, 96), W8(d, 104), W8(d, 112), W8(d, 120)
                 : "l"(da), "l"(db));
  else
    asm volatile("wgmma.mma_async.sync.aligned.m64n256k16.f32.bf16.bf16 " REGS128 ", %128, %129, 1, 1, 1, 0, 1;\n"
                 : R8(d, 0), R8(d, 8), R8(d, 16), R8(d, 24), R8(d, 32), R8(d, 40), R8(d, 48), R8(d, 56),
                   R8(d, 64), R8(d, 72), R8(d, 80), R8(d, 88), R8(d, 96), R8(d, 104), R8(d, 112), R8(d, 120)
                 : "l"(da), "l"(db));
}

__device__ __forceinline__ int fin_order(int e) {
  return e < 16 ? e + 8 : (e < 24 ? e - 16 : (e < 38 ? e + 8 : e - 14));
}

__device__ __forceinline__ void first_pairs(const Params& p, uint32_t sb, uint32_t rank, int cl) {
  const uint32_t item = p.sched[cl * MAXIT];
  const int nb = (item >> 3) & 31, row = (2 * (item & 7) + rank) * 128;
  const bool kv = (item >> 14) == IT_KV;
  const CUtensorMap* tma = kv ? &p.tm[TM_C] : &p.tm[TM_X];
  const CUtensorMap* tb0 = kv ? ((nb & 1) ? &p.tm[TM_WUV] : &p.tm[TM_WUK]) : &p.tm[TM_WG];
  const CUtensorMap* tb1 = kv ? tb0 : &p.tm[TM_WU];
  const int c0 = kv ? (nb >> 1) * 256 : nb * 128, c1 = kv ? c0 + 128 : c0;
#pragma unroll
  for (int kb = 0; kb < 4; kb++) {
    const int k2 = kb & 1, s0 = 3 * (kb >> 1);
    const uint32_t st = sb + (s0 + 2 * k2) * SLOT_BYTES, fb = sb + B_FULL + 8 * (s0 + 2 * k2), fa = sb + (k2 ? B_FULL1 : B_FULL) + 8 * (s0 + 1);
    mbar_expect_tx_el(fa, 16384);
    tma_load_2d_el(sb + (s0 + 1) * SLOT_BYTES + k2 * 16384, tma, kb * 64, row, fa);
    mbar_expect_tx_el(fb, SLOT_BYTES);
    tma_load_2d_el(st, tb0, c0, kb * 64, fb);
    tma_load_2d_el(st + 8192, tb0, c0 + 64, kb * 64, fb);
    tma_load_2d_el(st + 16384, tb1, c1, kb * 64, fb);
    tma_load_2d_el(st + 24576, tb1, c1 + 64, kb * 64, fb);
  }
}

__device__ __forceinline__ void producer(const Params& p, uint32_t sb, uint32_t rank, int cl) {
  int budget = WAIT_BUDGET;
  int slot = 0;
  uint32_t ph = 1, n = NSLOT, dep = 1;
  int att_cnt = 0;
  uint32_t st = 0, fb = 0;
  uint32_t e1 = 0x2d;
  auto begin = [&]() {
    st = sb + slot * SLOT_BYTES; fb = sb + B_FULL + 8 * slot;
    mbar_wait(sb + B_EMPTY1 + 8 * slot, (e1 >> slot) & 1);
    mbar_wait(sb + B_EMPTY + 8 * slot, ph ^ 1);
    mbar_expect_tx_el(fb, SLOT_BYTES);
  };
  auto begin_a0 = [&]() {
    st = sb + slot * SLOT_BYTES; fb = sb + B_FULL + 8 * slot;
    mbar_wait(sb + B_EMPTY + 8 * slot, ph ^ 1);
    mbar_expect_tx_el(fb, 16384);
  };
  auto begin_a1 = [&]() {
    st += 16384; fb = sb + B_FULL1 + 8 * slot;
    mbar_wait(sb + B_EMPTY1 + 8 * slot, (e1 >> slot) & 1);
    e1 ^= 1u << slot;
    mbar_expect_tx_el(fb, 16384);
  };
  auto end = [&]() {
    ++n;
    asm volatile("st.volatile.shared.u32 [%0], %1;" ::"r"(sb + B_ISS), "r"(n) : "memory");
    if (++slot == NSLOT) { slot = 0; ph ^= 1; }
  };
  for (int it = 0; it < MAXIT; it++) {
    const uint32_t item = p.sched[cl * MAXIT + it];
    const int type = item >> 14;
    if (type == IT_FIN) {
      const uint32_t tile = finq_wait_b<true>(sb + B_FINQ, budget);
      const int m = (tile & 14) + rank, ch = tile & 1;
#pragma unroll 1
      for (int i = 0; i < 47; i++) {
        const uint32_t e = finq_wait_b<true>(sb + B_FINQ + 4 + 4 * i, budget);
        if (e == FQ_END) break;
        fence_async_global();
        const int kp = e & 63;
        const CUtensorMap* tm = kp >= 32 ? &p.tm[TM_WD] : &p.tm[TM_WO];
        const int krow = (kp >= 32 ? kp - 32 : kp) * 128;
#pragma unroll 1
        for (int k2 = 0; k2 < 2; k2++) {
          begin();
          tma_load_2d_mc_el(st + rank * 16384, tm, ch * 256 + rank * 128, krow + k2 * 64, fb);
          tma_load_2d_mc_el(st + rank * 16384 + 8192, tm, ch * 256 + rank * 128 + 64, krow + k2 * 64, fb);
          end();
          if (k2 == 0) {
            begin_a0();
            bulk_load_el(st, g_a + ((size_t)(m * 46 + kp) << 15), 16384, fb);
            begin_a1();
            bulk_load_el(st, g_a + ((size_t)(m * 46 + kp) << 15) + 16384, 16384, fb);
            end();
          }
        }
      }
      break;
    }
    const int s = item & 7;
    const int m = 2 * s + rank;
    if (type != IT_ATT) {
      const int nb = (item >> 3) & 31;
      const CUtensorMap* tma = type == IT_KV ? &p.tm[TM_C] : &p.tm[TM_X];
      const CUtensorMap* tmb;
      int col;
      if (type == IT_KV) { tmb = (nb & 1) ? &p.tm[TM_WUV] : &p.tm[TM_WUK]; col = (nb >> 1) * 256 + rank * 128; }
      else { tmb = rank ? &p.tm[TM_WU] : &p.tm[TM_WG]; col = nb * 128; }
#pragma unroll 1
      for (int kp = it == 0 ? 2 : 0; kp < 4; kp++) {
#pragma unroll 1
        for (int k2 = 0; k2 < 2; k2++) {
          begin();
          tma_load_2d_mc_el(st + rank * 16384, tmb, col, kp * 128 + k2 * 64, fb);
          tma_load_2d_mc_el(st + rank * 16384 + 8192, tmb, col + 64, kp * 128 + k2 * 64, fb);
          end();
          if (k2 == 0) {
            begin_a0();
            tma_load_2d_el(st, tma, kp * 128, m * 128, fb);
            begin_a1();
            tma_load_2d_el(st, tma, kp * 128 + 64, m * 128, fb);
            end();
          }
        }
      }
    } else {
      const int h = (item >> 3) & 31;
      const int lo = 4 * s + rank, hi = 4 * s + 3 - rank;
      const int r0 = (att_cnt & 1) ? hi : lo, r1 = (att_cnt & 1) ? lo : hi;
      att_cnt++;
#pragma unroll 1
      for (int kb = 0; kb < 8; kb++) {
        begin();
        tma_load_2d_mc_el(st + 16384 + rank * 8192, &p.tm[TM_WQ], h * 128 + rank * 64, kb * 64, fb);
        tma_load_2d_el(st, &p.tm[TM_X64], kb * 64, r0 * 64, fb);
        tma_load_2d_el(st + 8192, &p.tm[TM_X64], kb * 64, r1 * 64, fb);
        end();
      }
      dep_wait(sb + B_DEP, ++dep);
      fence_async_global();
      const int nbk = 2 * s + 2;
      const uint8_t* kbase = g_kv + ((size_t)h << 19) + rank * 16384;
      const uint8_t* vbase = kbase + ((size_t)NH << 19);
#pragma unroll 1
      for (int i = 0; i < 2 * nbk; i++) {
        const uint8_t* src;
        if (i == 0) src = kbase;
        else if (i == 2 * nbk - 1) src = vbase + ((size_t)(nbk - 1) << 15);
        else if (i & 1) src = kbase + ((size_t)((i + 1) >> 1) << 15);
        else src = vbase + ((size_t)((i >> 1) - 1) << 15);
        begin();
        bulk_load_mc_el(st + rank * 16384, src, 16384, fb);
        end();
      }
    }
  }
}

__device__ __forceinline__ void scout(const Params& p, uint32_t sb, uint32_t rank, int cl, int lane) {
  int budget = WAIT_BUDGET;
  uint32_t n = 0, dep = 1;
  if (lane == 0) { flag_wait(&g_flags[FL_G], 256); st_release_smem(sb + B_DEP, 1); }
  __syncwarp();
  for (int it = 0; it < MAXIT; it++) {
    const uint32_t item = p.sched[cl * MAXIT + it];
    const int type = item >> 14;
    const int s = item & 7;
    if (type == IT_FIN) {
      if (rank != 0) break;
      const uint32_t rq = mapa(sb + B_FINQ, lane & 1);
      auto put = [&](int idx, uint32_t v) {
        if (lane < 2) asm volatile("st.release.cluster.shared::cluster.u32 [%0], %1;" ::"r"(rq + 4 * idx), "r"(v) : "memory");
      };
      auto put_relaxed = [&](int idx, uint32_t v) {
        if (lane < 2) asm volatile("st.relaxed.cluster.shared::cluster.u32 [%0], %1;" ::"r"(rq + 4 * idx), "r"(v) : "memory");
      };
      if (lane == 0) flag_wait(&g_flags[FL_Z], 256);
      dep_wait_b(sb + B_ISS, n - FIN_LEAD - 3, budget, 1000);
      dep_wait(sb + B_ISS, n - FIN_LEAD);
      uint32_t tile = 0;
      if (lane == 0) tile = atomicAdd(&g_flags[FL_FT], 1);
      tile = __shfl_sync(0xffffffffu, tile, 0);
      if (tile >= 64) {
        const uint32_t key = lane < 16 ? (ld_acquire(&g_flags[FL_FC + lane]) << 4 | lane) : 0xffffffffu;
        tile = __reduce_min_sync(0xffffffffu, key) & 15;
      } else {
        tile = (tile & 16) ? 15 - (tile & 15) : (tile & 15);
      }
      const unsigned* fl = &g_flags[FL_A + (tile >> 1)];
      uint32_t e = 0;
      if (lane == 0) e = atomicAdd(&g_flags[FL_FC + tile], 1);
      const uint32_t rdy0 = __ballot_sync(0xffffffffu, ld_acquire(fl + fin_order(lane) * 8) >= 4);
      const uint32_t rdy1 = __ballot_sync(0xffffffffu, lane < 14 && ld_acquire(fl + fin_order(32 + min(lane, 13)) * 8) >= 4);
      put(0, FQ_VALID | tile);
#pragma unroll 1
      for (int i = 0; i < 47; i++) {
        e = __shfl_sync(0xffffffffu, e, 0);
        if (e >= 46) { put_relaxed(1 + i, FQ_END); break; }
        const int kp = fin_order(e);
        const bool ready = e < 32 ? (rdy0 >> e) & 1 : (rdy1 >> (e - 32)) & 1;
        if (ready) {
          put_relaxed(1 + i, FQ_VALID | kp);
        } else {
          if (lane < 2) flag_wait(fl + kp * 8, 4);
          put(1 + i, FQ_VALID | kp);
        }
        __syncwarp();
        dep_wait(sb + B_ISS, n + 3 * (i + 1) - FIN_LEAD);
        if (lane == 0) e = atomicAdd(&g_flags[FL_FC + tile], 1);
      }
      break;
    } else if (type == IT_ATT) {
      const int h = (item >> 3) & 31;
      if (n + 8 > SCOUT_DIST) dep_wait_b(sb + B_ISS, n + 8 - SCOUT_DIST, budget, 1000);
      if (lane < 16 && (lane & 7) <= s) flag_wait(&g_flags[FL_KV + ((h >> 1) * 2 + (lane >> 3)) * 8 + (lane & 7)], 4);
      __syncwarp();
      ++dep;
      if (lane == 0) st_release_smem(sb + B_DEP, dep);
      n += 8 + 4 * s + 4;
    } else {
      n += 12;
    }
  }
}

__device__ __forceinline__ void storer(const Params& p, uint32_t sb, uint32_t rank, int cl, int c, int lane) {
  int budget = WAIT_BUDGET;
  const uint32_t stg = sb + STG_OFF + c * 16384;
  if (blockIdx.x < 128) {
    const int row = blockIdx.x * 16 + c * 8;
    mbar_wait(sb + B_FULL, 0);
    if (lane == 0) {
      mbar_expect_tx(sb + B_GATE + 8 * c, 8192);
      bulk_load(stg, p.x + (size_t)row * DM, 8192, sb + B_GATE + 8 * c);
    }
    const uint4* gw = reinterpret_cast<const uint4*>(p.gate_w);
    const uint4 wv0 = __ldg(gw + lane), wv1 = __ldg(gw + 32 + lane);
    mbar_wait(sb + B_GATE + 8 * c, 0);
    float mine = 0.f;
#pragma unroll 2
    for (int r = 0; r < 8; r++) {
      uint4 xv0, xv1;
      asm volatile("ld.shared.v4.u32 {%0,%1,%2,%3}, [%4];" : "=r"(xv0.x), "=r"(xv0.y), "=r"(xv0.z), "=r"(xv0.w) : "r"(stg + r * 1024 + lane * 16));
      asm volatile("ld.shared.v4.u32 {%0,%1,%2,%3}, [%4];" : "=r"(xv1.x), "=r"(xv1.y), "=r"(xv1.z), "=r"(xv1.w) : "r"(stg + r * 1024 + 512 + lane * 16));
      float acc = 0.f;
      auto dot = [&](uint32_t a, uint32_t b) {
        acc = fmaf(__uint_as_float(a << 16), __uint_as_float(b << 16), acc);
        acc = fmaf(__uint_as_float(a & 0xffff0000u), __uint_as_float(b & 0xffff0000u), acc);
      };
      dot(xv0.x, wv0.x); dot(xv0.y, wv0.y); dot(xv0.z, wv0.z); dot(xv0.w, wv0.w);
      dot(xv1.x, wv1.x); dot(xv1.y, wv1.y); dot(xv1.z, wv1.z); dot(xv1.w, wv1.w);
#pragma unroll
      for (int o = 16; o > 0; o >>= 1) acc += __shfl_xor_sync(0xffffffffu, acc, o);
      if (lane == r) mine = acc;
    }
    if (lane < 8) g_gate[row + lane] = 1.0f / (1.0f + __expf(-mine));
    __syncwarp();
    if (lane == 0) { mbar_arrive(sb + B_STGE + 8 * c); red_release(&g_flags[FL_G], 1); }
  } else if (lane == 0) {
    mbar_arrive(sb + B_STGE + 8 * c);
  }
  uint32_t ph = 0;
  int att_cnt = 0;
  for (int it = 0; it < MAXIT; it++) {
    const uint32_t item = p.sched[cl * MAXIT + it];
    const int type = item >> 14;
    if (it == 5) {
      __syncwarp();
      if (blockIdx.x < 128) {
        uint4* oz = reinterpret_cast<uint4*>(p.out + (size_t)(blockIdx.x * 16 + c * 8) * DM);
#pragma unroll 4
        for (int r = 0; r < 16; r++) oz[r * 32 + lane] = make_uint4(0, 0, 0, 0);
        __syncwarp();
        if (lane == 0) red_release(&g_flags[FL_Z], 1);
      }
    }
    if (type == IT_FIN) break;
    if (lane != 0) continue;
    const int s = item & 7, nb = (item >> 3) & 31;
    const int m = 2 * s + rank;
    uint8_t* dst;
    int flag, rounds = 1;
    if (type == IT_KV) {
      dst = g_kv + ((size_t)((nb & 1) * NH + (nb >> 1) * 2) << 19) + ((size_t)m << 15) + c * 8192;
      flag = FL_KV + nb * 8 + s;
      rounds = 2;
    } else if (type == IT_UP) {
      dst = g_a + ((size_t)(m * 46 + 32 + nb) << 15) + c * 8192;
      flag = FL_A + (32 + nb) * 8 + s;
    } else {
      const bool is_hi = ((att_cnt & 1) ^ c) != 0;
      att_cnt++;
      const int r = is_hi ? 4 * s + 3 - rank : 4 * s + rank;
      dst = g_a + ((size_t)((r >> 1) * 46 + nb) << 15) + (r & 1) * 8192;
      flag = FL_A + nb * 8 + s;
    }
#pragma unroll 1
    for (int rd = 0; rd < rounds; rd++) {
      mbar_wait(sb + B_STGF + 8 * c, ph);
      ph ^= 1;
      bulk_store(dst, stg, 8192);
      bulk_store(dst + 16384, stg + 8192, 8192);
      bulk_commit();
      bulk_wait_read();
      mbar_arrive(sb + B_STGE + 8 * c);
      dst += (size_t)1 << 19;
    }
    bulk_wait_all();
    red_release(&g_flags[flag], 1);
  }
}

__device__ __forceinline__ void consumer(const Params& p, uint32_t sb, uint32_t rank, int cl, int c, int w) {
  const uint32_t sb16 = (sb & 0x3FFFF) >> 4;
  int budget = WAIT_BUDGET;
  uint32_t stsm_off, rel;
  {
    const int lane = lane_id();
    stsm_off = (w * 16 + (lane & 7) + ((lane >> 3) & 1) * 8) * 128 + (((lane >> 4) ^ (lane & 7)) << 4);
    rel = lane < 2 ? mapa(sb + B_EMPTY, lane) : 0;
  }
  const uint32_t stg = sb + STG_OFF + c * 16384;
  uint32_t sph = 0;
  auto release = [&](int slot) { if (rel != 0) mbar_arrive_cluster(rel + 8 * slot); };
  auto stsm_tile = [&](uint32_t base, const uint32_t (&pk)[32]) {
    uint32_t off = stsm_off;
    asm volatile("" : "+r"(off));
#pragma unroll
    for (int kk = 0; kk < 8; kk++)
      stsm4(base + (kk >> 2) * 8192 + (off ^ ((kk & 3) << 5)), pk[4 * kk], pk[4 * kk + 1], pk[4 * kk + 2], pk[4 * kk + 3]);
  };
  auto stage_store = [&](const uint32_t (&pk)[32]) {
    mbar_wait(sb + B_STGE + 8 * c, sph);
    sph ^= 1;
    stsm_tile(stg, pk);
    fence_async_smem();
    mbar_arrive_el(sb + B_STGF + 8 * c);
  };
  bool gate_ok = false;
  int as = 0;
  uint32_t aph = 0, f1 = 0;
  auto adv = [&]() { if (++as == NSLOT) { as = 0; aph ^= 1; } };
  auto wait_full = [&]() { mbar_wait(sb + B_FULL + 8 * as, aph); };
  int att_cnt = 0;
  uint32_t P[32], P2[32];
  int dk = 0;
#pragma unroll
  for (int i = 0; i < 32; i++) { P[i] = 0; P2[i] = 0; }
  auto flush1 = [&]() { if (dk == 1 || dk == 2) { stage_store(P); dk = dk == 2 ? 4 : 0; } };
  auto flush2 = [&](bool must) {
    if (dk == 4 && (must || __all_sync(0xffffffffu, mbar_test(sb + B_STGE + 8 * c, sph)))) { stage_store(P2); dk = 0; }
  };
  uint32_t item = p.sched[cl * MAXIT];
  for (int it = 0; it < MAXIT; it++) {
    const int type = item >> 14;
    const int s = item & 7;
    item = p.sched[cl * MAXIT + min(it + 1, MAXIT - 1)];
    if (type != IT_ATT) {
      float acc[128];
      int sa = 0, sb0 = 0, sb1 = 0;
      auto kblock = [&](auto init, int aoff, int bslot) {
        const uint32_t da = sb16 + sa * (SLOT_BYTES >> 4) + c * 512 + aoff, db = sb16 + bslot * (SLOT_BYTES >> 4);
        WG_FENCE();
        wgmma_ss_n256<decltype(init)::value>(acc, mk_desc(da, 0, 16), mk_desc(db, 0, 8192));
#pragma unroll
        for (int kk = 1; kk < 4; kk++) wgmma_ss_n256<0>(acc, mk_desc(da, kk * 32, 16), mk_desc(db, kk * 2048, 8192));
        WG_COMMIT();
      };
      if (type == IT_FIN) {
        if (finq_wait(sb + B_FINQ + 4) == FQ_END) break;
      }
      auto wait_a1 = [&]() { mbar_wait(sb + B_FULL1 + 8 * sa, (f1 >> sa) & 1); f1 ^= 1u << sa; };
      sb0 = as; wait_full(); adv();
      sa = as; wait_full(); adv();
      kblock(IC<1>(), 0, sb0);
      wait_a1();
      uint32_t pb_ph = 0, b1_ph = aph;
      sb1 = as; wait_full(); adv();
      kblock(IC<0>(), 1024, sb1);
      WG_WAIT(1);
      release(sb0); release(sa);
      flush1();
      int pb = -1;
#pragma unroll 1
      for (int kp = 1;; kp++) {
        if (type == IT_FIN ? finq_wait(sb + B_FINQ + 4 + 4 * kp) == FQ_END : kp == 4) break;
        pb = sb1; pb_ph = b1_ph;
        WG_WAIT(0);
        release(sa + NSLOT); release(pb);
        sb0 = as; wait_full(); adv();
        sa = as; wait_full(); adv();
        kblock(IC<0>(), 0, sb0);
        WG_WAIT(0);
        release(sb0); release(sa);
        wait_a1();
        sb1 = as; b1_ph = aph; wait_full(); adv();
        kblock(IC<0>(), 1024, sb1);
        flush2(kp == 3);
      }
      if (type == IT_FIN) {
        const uint32_t tile = finq_wait_b<true>(sb + B_FINQ, budget);
        const int col = (tile & 1) * 256, row = ((tile & 14) + rank) * 128 + c * 64 + w * 16;
        const bool l0 = lane_id() == 0;
        fence_async_global();
        mbar_wait(sb + B_STGE + 8 * c, sph);
        if (pb >= 0) mbar_wait(sb + B_EMPTY + 8 * pb, pb_ph);
        WG_WAIT(0);
        reg_fence(acc);
        release(sa + NSLOT); release(sb1);
        uint32_t off = stsm_off;
        asm volatile("" : "+r"(off));
#pragma unroll
        for (int q = 0; q < 4; q++) {
          if (q == 2 && pb < 0) { pb = sb1; mbar_wait(sb + B_EMPTY + 8 * pb, b1_ph); }
          const uint32_t dst = (q < 2 ? stg : sb + pb * SLOT_BYTES + c * 16384) + (q & 1) * 8192;
#pragma unroll
          for (int kk = 0; kk < 4; kk++) {
            const int i = 32 * q + 8 * kk;
            stsm4(dst + (off ^ (kk << 5)), pack_bf16(acc[i], acc[i + 1]), pack_bf16(acc[i + 2], acc[i + 3]),
                  pack_bf16(acc[i + 4], acc[i + 5]), pack_bf16(acc[i + 6], acc[i + 7]));
          }
          fence_async_smem();
          __syncwarp();
          if (l0) tma_reduce_add_2d(&p.tm[TM_OUT], col + 64 * q, row, dst + w * 2048);
        }
        if (l0) { bulk_commit(); bulk_wait_read(); }
        __syncwarp();
        break;
      }
      float dg0 = 0.f, dg1 = 0.f;
      if (type == IT_UP) {
        if (!gate_ok) { dep_wait(sb + B_DEP, 1); gate_ok = true; }
        const int row = (2 * s + rank) * 128 + c * 64 + w * 16 + (lane_id() >> 2);
        dg0 = 0.5f - 0.5f * __ldcg(&g_gate[row]);
        dg1 = 0.5f - 0.5f * __ldcg(&g_gate[row + 8]);
      }
      WG_WAIT(0);
      reg_fence(acc);
      release(sa + NSLOT); release(sb1);
      if (type == IT_UP) {
#pragma unroll
        for (int i = 0; i < 32; i++) {
          float hv[2];
#pragma unroll
          for (int e = 0; e < 2; e++) {
            const float gt = acc[2 * i + e], up = acc[64 + 2 * i + e];
            const float u = gt * fmaf(gt * gt, 0.044715f * 0.7978845608028654f, 0.7978845608028654f);
            const float hg = gt * up * ((i & 1) ? dg1 : dg0);
            hv[e] = fmaf(hg, tanh_fast(u), hg);
          }
          P[i] = pack_bf16(hv[0], hv[1]);
        }
      } else {
#pragma unroll
        for (int i = 0; i < 32; i++) {
          P[i] = pack_bf16(acc[2 * i], acc[2 * i + 1]);
          P2[i] = pack_bf16(acc[64 + 2 * i], acc[64 + 2 * i + 1]);
        }
      }
      dk = type == IT_KV ? 2 : 1;
    } else {
      const bool is_hi = ((att_cnt & 1) ^ c) != 0;
      att_cnt++;
      const int r = is_hi ? 4 * s + 3 - rank : 4 * s + rank;
      const int nb = (r >> 1) + 1;
      float S[64], O[64];
      auto qblock = [&](auto init, int slot) {
        const uint32_t st = sb16 + slot * (SLOT_BYTES >> 4);
        WG_FENCE();
        wgmma_ss_n128<1, decltype(init)::value>(S, mk_desc(st + c * 512, 0, 16), mk_desc(st, 16384, 8192));
#pragma unroll
        for (int kk = 1; kk < 4; kk++)
          wgmma_ss_n128<1, 0>(S, mk_desc(st + c * 512, kk * 32, 16), mk_desc(st, 16384 + kk * 2048, 8192));
        WG_COMMIT();
      };
      {
        int prev = as;
        wait_full(); adv();
        qblock(IC<1>(), prev);
#pragma unroll 1
        for (int kb = 1; kb < 8; kb++) {
          WG_WAIT(0);
          release(prev);
          prev = as;
          wait_full(); adv();
          qblock(IC<0>(), prev);
          flush2(kb == 7);
        }
        wait_full();
        WG_WAIT(0);
        reg_fence(S);
        release(prev);
#pragma unroll
        for (int i = 0; i < 32; i++) P2[i] = pack_bf16(S[2 * i], S[2 * i + 1]);
      }
      const float cs = 0.08838834764831845f * 1.4426950408889634f;
      float nm0 = 0.f, nm1 = 0.f, l0 = 0.f, l1 = 0.f, s0, s1;
      const float LAZY_T = 65536.f;
      const uint32_t q16 = sb16 + ((STG_OFF + c * 16384) >> 4);

      auto issue_qk = [&](int slot) {
        const uint32_t st = sb16 + slot * (SLOT_BYTES >> 4);
        wgmma_ss_n128<0, 2>(S, mk_desc(q16, 0, 16), mk_desc(st, 0, 16));
#pragma unroll
        for (int kk = 1; kk < 8; kk++)
          wgmma_ss_n128<0, 0>(S, mk_desc(q16, (kk >> 2) * 8192 + (kk & 3) * 32, 16), mk_desc(st, (kk >> 2) * 16384 + (kk & 3) * 32, 16));
        WG_COMMIT();
      };
      auto issue_qk_rs = [&](auto init, float (&D)[64], int slot) {
        const uint32_t st = sb16 + slot * (SLOT_BYTES >> 4);
        wgmma_rs_n128<0, decltype(init)::value>(D, P2[0], P2[1], P2[2], P2[3], mk_desc(st, 0, 16));
#pragma unroll
        for (int kk = 1; kk < 8; kk++)
          wgmma_rs_n128<0, 0>(D, P2[4 * kk], P2[4 * kk + 1], P2[4 * kk + 2], P2[4 * kk + 3], mk_desc(st, (kk >> 2) * 16384 + (kk & 3) * 32, 16));
        WG_COMMIT();
      };
      auto issue_pv = [&](auto init, int slot, uint32_t (&Pc)[32]) {
        const uint32_t st = sb16 + slot * (SLOT_BYTES >> 4);
        wgmma_rs_n128<1, decltype(init)::value>(O, Pc[0], Pc[1], Pc[2], Pc[3], mk_desc(st, 0, 16384));
#pragma unroll
        for (int kk = 1; kk < 8; kk++)
          wgmma_rs_n128<1, 0>(O, Pc[4 * kk], Pc[4 * kk + 1], Pc[4 * kk + 2], Pc[4 * kk + 3], mk_desc(st, kk * 2048, 16384));
        WG_COMMIT();
      };
      auto mask = [&](float (&X)[64]) {
        const int lane = lane_id();
        const float nthr = -(float)(w * 16 + (lane >> 2) + (r & 1) * 64 - (lane & 3) * 2);
#pragma unroll
        for (int e = 0; e < 2; e++) {
          float mprev = __saturatef(nthr + (float)(e - 8));
#pragma unroll
          for (int j = 0; j < 16; j++) {
            const float mk = __saturatef(nthr + (float)(8 * j + e));
            X[4 * j + e] = fmaf(mk, -1e30f, X[4 * j + e]);
            X[4 * j + 2 + e] = fmaf(mprev, -1e30f, X[4 * j + 2 + e]);
            mprev = mk;
          }
        }
      };
      auto row_max = [&](auto ng, const float (&X)[64], float& a0, float& a1) {
        float b0, b1;
        a0 = fmaxf(X[0], X[1]); a1 = fmaxf(X[2], X[3]); b0 = fmaxf(X[4], X[5]); b1 = fmaxf(X[6], X[7]);
#pragma unroll
        for (int j = 2; j < decltype(ng)::value; j += 2) {
          a0 = fmaxf(a0, fmaxf(X[4 * j], X[4 * j + 1]));
          a1 = fmaxf(a1, fmaxf(X[4 * j + 2], X[4 * j + 3]));
          b0 = fmaxf(b0, fmaxf(X[4 * j + 4], X[4 * j + 5]));
          b1 = fmaxf(b1, fmaxf(X[4 * j + 6], X[4 * j + 7]));
        }
        a0 = fmaxf(a0, b0); a1 = fmaxf(a1, b1);
        a0 = fmaxf(a0, __shfl_xor_sync(0xffffffffu, a0, 1));
        a1 = fmaxf(a1, __shfl_xor_sync(0xffffffffu, a1, 1));
        a0 = fmaxf(a0, __shfl_xor_sync(0xffffffffu, a0, 2));
        a1 = fmaxf(a1, __shfl_xor_sync(0xffffffffu, a1, 2));
        a0 *= cs; a1 *= cs;
      };
      auto exp_pack = [&](const float (&X)[64], uint32_t (&Pn)[32]) {
        s0 = 0.f; s1 = 0.f;
#pragma unroll
        for (int j = 0; j < 16; j++) {
          const float e0 = ex2(fmaf(X[4 * j], cs, nm0)), e1 = ex2(fmaf(X[4 * j + 1], cs, nm0));
          const float e2 = ex2(fmaf(X[4 * j + 2], cs, nm1)), e3 = ex2(fmaf(X[4 * j + 3], cs, nm1));
          s0 += e0 + e1;
          s1 += e2 + e3;
          Pn[2 * j] = pack_bf16(e0, e1);
          Pn[2 * j + 1] = pack_bf16(e2, e3);
        }
      };
      bool sig = is_hi;
      auto body = [&](auto first, uint32_t (&Pc)[32], uint32_t (&Pn)[32], bool last) {
        int vs;
        reg_fence_u(Pc);
        if (decltype(first)::value) {
          vs = as;
          adv();
          WG_FENCE();
          issue_pv(IC<2>(), vs, Pc);
          mbar_wait(sb + B_STGE + 8 * c, sph);
          stsm_tile(stg, Pn);
        } else {
          const int ks = as;
          adv();
          vs = as;
          reg_fence(O);
          WG_FENCE();
          issue_qk(ks);
          wait_full();
          adv();
          WG_FENCE();
          issue_pv(IC<0>(), vs, Pc);
          if (sig) { asm volatile("bar.arrive 5, 256;" ::: "memory"); sig = false; }
          WG_WAIT(1);
          reg_fence(S);
          release(ks);
        }
        if (last) mask(S);
        exp_pack(S, Pn);
        reg_fence_u(Pn);
        wait_full();
        WG_WAIT(0);
        reg_fence(O);
        reg_fence_u(Pc);
        if (__builtin_expect(__any_sync(0xffffffffu, !(s0 <= LAZY_T && s1 <= LAZY_T)), 0)) {
          float a0, a1;
          row_max(IC<16>(), S, a0, a1);
          a0 = fminf(-a0, nm0); a1 = fminf(-a1, nm1);
          const float sc0 = ex2(a0 - nm0), sc1 = ex2(a1 - nm1);
          nm0 = a0; nm1 = a1;
          l0 *= sc0; l1 *= sc1;
#pragma unroll
          for (int i = 0; i < 16; i++) {
            O[4 * i] *= sc0; O[4 * i + 1] *= sc0; O[4 * i + 2] *= sc1; O[4 * i + 3] *= sc1;
          }
          exp_pack(S, Pn);
        }
        release(vs);
        l0 += s0; l1 += s1;
      };

      const int k0 = as;
      adv();
      const int k1 = as;
      wait_full();
      adv();
      if (!is_hi) asm volatile("bar.sync 4, 256;" ::: "memory");
      reg_fence_u(P2);
      WG_FENCE();
      issue_qk_rs(IC<1>(), O, k0);
      issue_qk_rs(IC<2>(), S, k1);
      if (is_hi) asm volatile("bar.arrive 4, 256;" ::: "memory");
      WG_WAIT(1);
      reg_fence(O);
      release(k0);
      if (nb == 1) mask(O);
      row_max(IC<4>(), O, nm0, nm1);
      nm0 = -nm0; nm1 = -nm1;
      exp_pack(O, P);
      if (__builtin_expect(__any_sync(0xffffffffu, !(s0 <= LAZY_T && s1 <= LAZY_T)), 0)) {
        row_max(IC<16>(), O, nm0, nm1);
        nm0 = -nm0; nm1 = -nm1;
        exp_pack(O, P);
      }
      l0 = s0; l1 = s1;
      reg_fence_u(P);
      wait_full();
      WG_WAIT(0);
      reg_fence(S);
      reg_fence_u(P2);
      release(k1);
      float f0, f1;
      auto finish = [&](uint32_t (&Pc)[32]) {
        reg_fence_u(Pc);
        reg_fence(O);
        WG_FENCE();
        issue_pv(IC<0>(), as, Pc);
        if (sig) asm volatile("bar.arrive 5, 256;" ::: "memory");
        if (!gate_ok) { dep_wait(sb + B_DEP, 1); gate_ok = true; }
        const int qrow = r * 64 + w * 16 + (lane_id() >> 2);
        const float gt0 = __ldcg(&g_gate[qrow]), gt1 = __ldcg(&g_gate[qrow + 8]);
        l0 += __shfl_xor_sync(0xffffffffu, l0, 1); l1 += __shfl_xor_sync(0xffffffffu, l1, 1);
        l0 += __shfl_xor_sync(0xffffffffu, l0, 2); l1 += __shfl_xor_sync(0xffffffffu, l1, 2);
        f0 = __fdividef(gt0, l0); f1 = __fdividef(gt1, l1);
        WG_WAIT(0);
        reg_fence(O);
        reg_fence_u(Pc);
        release(as);
        adv();
      };
      if (nb == 1) {
#pragma unroll
        for (int i = 0; i < 64; i++) O[i] = 0.f;
        asm volatile("bar.sync 5, 256;" ::: "memory");
      } else {
        body(IC<1>(), P, P2, nb == 2);
        fence_async_smem();
        asm volatile("bar.sync %0, 128;" ::"r"(c + 1) : "memory");
        if (!is_hi) asm volatile("bar.sync 5, 256;" ::: "memory");
#pragma unroll 1
        for (int j = 2; j + 1 < nb; j += 2) {
          body(IC<0>(), P2, P, false);
          body(IC<0>(), P, P2, j + 2 == nb);
        }
        if (!is_hi) {
          body(IC<0>(), P2, P, true);
          release(as);
          adv();
          wait_full();
        }
      }
      if (is_hi) {
        finish(P2);
      } else {
        finish(P);
        wait_full();
        release(as);
        adv();
      }
#pragma unroll
      for (int i = 0; i < 16; i++) {
        P[2 * i] = pack_bf16(O[4 * i] * f0, O[4 * i + 1] * f0);
        P[2 * i + 1] = pack_bf16(O[4 * i + 2] * f1, O[4 * i + 3] * f1);
      }
      dk = 1;
    }
    if ((item >> 14) >= IT_ATT) flush1();
  }
}

__global__ void __cluster_dims__(2, 1, 1) __launch_bounds__(384, 1) mega_kernel(const __grid_constant__ Params p) {
  extern __shared__ uint8_t smem_raw[];
  const uint32_t sb = (smem_u32(smem_raw) + 1023) & ~1023u;
  const int warp = __shfl_sync(0xffffffffu, threadIdx.x >> 5, 0);
  uint32_t rank;
  asm volatile("mov.u32 %0, %%cluster_ctarank;" : "=r"(rank));
  const int cl = blockIdx.x >> 1;
  if (warp == 0) {
    const int lane = lane_id();
    if (lane == 0) {
#pragma unroll
      for (int i = 0; i < NSLOT; i++) {
        mbar_init(sb + B_FULL + 8 * i, 1); mbar_init(sb + B_EMPTY + 8 * i, 16);
        mbar_init(sb + B_FULL1 + 8 * i, 1); mbar_init(sb + B_EMPTY1 + 8 * i, 16);
      }
#pragma unroll
      for (int i = 0; i < 2; i++) { mbar_init(sb + B_STGF + 8 * i, 4); mbar_init(sb + B_STGE + 8 * i, 1); mbar_init(sb + B_GATE + 8 * i, 1); }
    }
    for (int i = lane; i < 50; i += 32) asm volatile("st.shared.u32 [%0], %1;" ::"r"(sb + B_DEP + 4 * i), "r"(0) : "memory");
    asm volatile("fence.mbarrier_init.release.cluster;" ::: "memory");
    fence_async_smem();
  }
  else if (warp == 1) {
    const int lane = lane_id();
    if (lane < TM_COUNT) asm volatile("prefetch.tensormap [%0];" ::"l"(&p.tm[lane]) : "memory");
  }
  __syncthreads();
  if (warp < 4) {
    if (warp == 3) cluster_arrive_release(); else cluster_arrive_relaxed();
    asm volatile("setmaxnreg.dec.sync.aligned.u32 40;");
    if (warp == 0) first_pairs(p, sb, rank, cl);
    cluster_wait();
    if (warp == 0) producer(p, sb, rank, cl);
    else {
      const int lane = lane_id();
      if (warp == 1) {
        scout(p, sb, rank, cl, lane);
        __syncwarp();
        unsigned t = 0;
        if (lane == 0) { __threadfence(); t = atomicAdd(&g_flags[FL_TICKET], 1); }
        t = __shfl_sync(0xffffffffu, t, 0);
        if (t == gridDim.x - 1) {
          __threadfence();
          for (int i = lane; i < FL_TOTAL; i += 32) g_flags[i] = 0;
        }
      } else {
        storer(p, sb, rank, cl, warp - 2, lane);
      }
    }
    __syncwarp();
    cluster_sync_relaxed();
  } else {
    cluster_arrive_relaxed();
    asm volatile("setmaxnreg.inc.sync.aligned.u32 232;");
    cluster_wait();
    consumer(p, sb, rank, cl, (warp >> 2) - 1, warp & 3);
    cluster_sync_relaxed();
  }
}

typedef CUresult (*EncodeFn)(CUtensorMap*, CUtensorMapDataType, cuuint32_t, void*, const cuuint64_t*, const cuuint64_t*,
                             const cuuint32_t*, const cuuint32_t*, CUtensorMapInterleave, CUtensorMapSwizzle,
                             CUtensorMapL2promotion, CUtensorMapFloatOOBfill);

void make_map(EncodeFn enc, CUtensorMap* tm, const void* ptr, int rows, int cols, int box_rows) {
  cuuint64_t gd[2] = {(cuuint64_t)cols, (cuuint64_t)rows};
  cuuint64_t gs[1] = {(cuuint64_t)cols * 2};
  cuuint32_t box[2] = {64, (cuuint32_t)box_rows};
  cuuint32_t es[2] = {1, 1};
  enc(tm, CU_TENSOR_MAP_DATA_TYPE_BFLOAT16, 2, const_cast<void*>(ptr), gd, gs, box, es, CU_TENSOR_MAP_INTERLEAVE_NONE,
      CU_TENSOR_MAP_SWIZZLE_128B, CU_TENSOR_MAP_L2_PROMOTION_NONE, CU_TENSOR_MAP_FLOAT_OOB_FILL_NONE);
}

void build_sched(uint16_t* sched) {
  const double C_UP = 10800, C_ATTS = 4400;
  int cnt[MAXCL];
  for (int c = 0; c < MAXCL; c++) cnt[c] = 0;
  auto push = [&](int c, int item) { sched[c * MAXIT + cnt[c]++] = (uint16_t)item; };
  auto push_kv = [&](int g) { for (int j = 0; j < 64; j++) push(2 + j, (IT_KV << 14) | (g * 64 + j)); };
  auto second = [&](int u) { return ((u - 64) & 7) * 8 + 7 - ((u - 64) >> 3); };
  auto push_up = [&]() {
    int u = 0;
    for (; u < 112 - 2 * AUX_UP; u++) push(2 + (u < 64 ? u : second(u)), (IT_UP << 14) | u);
    for (; u < 112; u++) push(u & 1, (IT_UP << 14) | u);
  };
  int sv[4][64];
  bool heavy[64];
  for (int j = 0; j < 64; j++) heavy[j] = false;
  for (int u = 64; u < 112 - 2 * AUX_UP; u++) heavy[second(u)] = true;
  for (int j = 0; j < 64; j++) { sv[0][j] = 7 - (j & 7); sv[1][j] = j & 7; sv[2][j] = 7 - (j & 7); sv[3][j] = j & 7; }
  {
    const int up2[8] = {2, 3, 4, 5, 6, 7, 7, 6}, dn2[8] = {1, 0, 0, 1, 2, 3, 4, 5};
    const int up1[8] = {1, 2, 3, 4, 5, 6, 7, 7}, dn1[8] = {0, 0, 1, 2, 3, 4, 5, 6};
    for (int j = 0; j < 64; j++) {
      const int g = j >> 3, i = j & 7;
      sv[1][j] = g == 0 || g == 4 ? up2[i] : g == 1 || g == 5 ? dn2[i] : g == 2 ? up1[i] : g == 3 ? dn1[i] : i;
    }
  }
  auto cost = [&](int j) { return (heavy[j] ? C_UP : 0.0) + C_ATTS * (sv[0][j] + sv[1][j] + sv[2][j] + sv[3][j]); };
  for (int iter = 0; iter < 200; iter++) {
    bool any = false;
    for (int a = 0; a < 64; a++)
      for (int b = 0; b < 64; b++)
        for (int r = 2; r < 4; r++) {
          const double ca = cost(a), cb = cost(b);
          const int t0 = sv[r][a]; sv[r][a] = sv[r][b]; sv[r][b] = t0;
          const double na = cost(a), nb2 = cost(b);
          if (na * na + nb2 * nb2 < ca * ca + cb * cb - 1.0) any = true;
          else { const int t1 = sv[r][a]; sv[r][a] = sv[r][b]; sv[r][b] = t1; }
        }
    if (!any) break;
  }
  auto push_att = [&](int rnd) {
    int used[8] = {0, 0, 0, 0, 0, 0, 0, 0};
    for (int c = 0; c < 64; c++) {
      const int s = sv[rnd][c], h = rnd * 8 + used[s]++;
      push(c + 2, (IT_ATT << 14) | (h << 3) | s);
    }
  };
  push_kv(1); push_kv(0);
  push_up(); push_att(0); push_kv(2); push_kv(3); push_att(1);
  push_att(2); push_att(3);
  for (int c = 0; c < MAXCL; c++)
    for (int i = cnt[c]; i < MAXIT; i++) sched[c * MAXIT + i] = (uint16_t)(IT_FIN << 14);
}

}

extern "C" void kernel_launch(void* const* d_in, const int* in_sizes, int n_in, void* d_out, int out_size) {
  (void)in_sizes; (void)n_in; (void)out_size;
  static Params p;
  static bool init = false;
  static const void* key[12];
  bool same = init;
  for (int i = 0; i < 11 && same; i++) same = key[i] == d_in[i];
  same = same && key[11] == d_out;
  if (!same) {
    EncodeFn enc = nullptr;
    cudaDriverEntryPointQueryResult qr;
    cudaGetDriverEntryPoint("cuTensorMapEncodeTiled", (void**)&enc, cudaEnableDefault, &qr);
    make_map(enc, &p.tm[TM_X64], d_in[0], SEQ, DM, 64);
    make_map(enc, &p.tm[TM_X], d_in[0], SEQ, DM, 128);
    make_map(enc, &p.tm[TM_C], d_in[1], SEQ, DM, 128);
    make_map(enc, &p.tm[TM_WQ], d_in[2], DM, NH * 128, 64);
    make_map(enc, &p.tm[TM_WUK], d_in[3], DM, NH * 128, 64);
    make_map(enc, &p.tm[TM_WUV], d_in[4], DM, NH * 128, 64);
    make_map(enc, &p.tm[TM_WO], d_in[5], NH * 128, DM, 64);
    make_map(enc, &p.tm[TM_WG], d_in[7], DM, FF, 64);
    make_map(enc, &p.tm[TM_WU], d_in[8], DM, FF, 64);
    make_map(enc, &p.tm[TM_WD], d_in[9], FF, DM, 64);
    make_map(enc, &p.tm[TM_OUT], d_out, SEQ, DM, 16);
    p.x = (const __nv_bfloat16*)d_in[0];
    p.gate_w = (const __nv_bfloat16*)d_in[10];
    p.out = (__nv_bfloat16*)d_out;
    build_sched(p.sched);
    cudaFuncSetAttribute(mega_kernel, cudaFuncAttributeMaxDynamicSharedMemorySize, SMEM_BYTES);
    for (int i = 0; i < 11; i++) key[i] = d_in[i];
    key[11] = d_out;
    init = true;
  }
  mega_kernel<<<2 * MAXCL, 384, SMEM_BYTES>>>(p);
}
```
